```python
import torch

def _softmax(x, axis=-1):
    return torch.softmax(x, dim=axis)
def _gelu(x):
    return torch.nn.functional.gelu(x, approximate="tanh")
def _silu(x):
    return torch.nn.functional.silu(x)
def _sigmoid(x):
    return torch.sigmoid(x)
def _layernorm(x, axis=-1, eps=1e-5):
    m = x.mean(dim=axis, keepdim=True)
    v = x.var(dim=axis, keepdim=True, unbiased=False)
    return (x - m) / torch.sqrt(v + eps)
def _scatter_add(tgt, idx, src, axis=0):
    return tgt.clone().index_add_(axis, idx, src)
def _segment_sum(src, seg, n):
    out = torch.zeros((n,) + src.shape[1:], dtype=src.dtype)
    return out.index_add_(0, seg, src)
def _pad(x, pw):
    flat = tuple(v for pair in reversed(pw) for v in pair)
    return torch.nn.functional.pad(x, flat)

kernel_name = 'standalone__controlnet__diffusion'

def setup_inputs():

    _w = (lambda a: (lambda t: t.to(torch.bfloat16) if t.is_floating_point() else t)(torch.as_tensor(a)))
    B, HW, C = 2, 64, 512
    sc = C ** -0.5
    return {
        "x_frozen": _w((lambda *s: torch.randn(*s, dtype=torch.bfloat16) * 0.1)(B, HW, HW, C)),
        "x": _w((lambda *s: torch.randn(*s, dtype=torch.bfloat16) * 0.2)(B, HW, HW, C)),
        "c": _w((lambda *s: torch.randn(*s, dtype=torch.bfloat16) * 0.8)(B, HW, HW, C)),
        "w_z1": _w((lambda *s: torch.randn(*s, dtype=torch.bfloat16) * 0.8)(C, C) * sc),
        "w_z2": _w((lambda *s: torch.randn(*s, dtype=torch.bfloat16) * 0.2)(C, C) * sc),
        "w_conv": _w((lambda *s: torch.randn(*s, dtype=torch.bfloat16) * 0.2)(3, 3, C, C) * sc / 3.0),
    }

def reference(x_frozen, x, c, w_z1, w_z2, w_conv):
    B, H, W, C = x.shape
    h_in = x + torch.einsum("bhwc,cd->bhwd", c, w_z1)
    h = _silu(_layernorm(h_in, axis=-1))
    hp = _pad(h, ((0, 0), (1, 1), (1, 1), (0, 0)))
    acc = h * 0.0
    for di in range(3):
        for dj in range(3):
            acc = acc + torch.einsum("bhwc,cd->bhwd", hp[:, di:di + H, dj:dj + W, :], w_conv[di, dj])
    h = h_in + acc
    return x_frozen + torch.einsum("bhwc,cd->bhwd", h, w_z2)
```

```cpp
#include <cuda_runtime.h>
#include <cuda_bf16.h>
#include <cuda.h>
#include <stdint.h>

namespace {

constexpr int SLOT = 32768, NSLOT = 5, FSLOT = 34816;
constexpr int OFF_A = NSLOT * SLOT;
constexpr int OFF_STATS = OFF_A + 65536;
constexpr int OFF_BAR = OFF_STATS + 1024;
constexpr int NSEQ = 84;
constexpr int B_FULL = 0, B_EMPTY = NSEQ, B_FFULL = 2 * NSEQ, B_FEMPTY = B_FFULL + 8, B_CFULL = B_FEMPTY + 8,
              B_HIN = B_CFULL + 8, B_STAGED = B_HIN + 2, B_BASE = B_STAGED + 2, B_UDONE = B_BASE + 2,
              B_VDONE = B_UDONE + 1, B_VU = B_VDONE + 1, B_XDONE = B_VU + 1, B_XRDY = B_XDONE + 2, NBAR = B_XRDY + 2;
constexpr int SMEM_BYTES = OFF_BAR + NBAR * 8;
static_assert(SMEM_BYTES <= 232448, "smem");
constexpr int LEAD = 2;

constexpr int VB = 18432, UB = 12288;
constexpr int V_KC = 132 * 1024, V_POS = 16 * V_KC;

constexpr float WA = 2.0f / 3.0f, WB = 1.5f, WA2 = 4.0f / 9.0f, WB2 = 2.25f, WS = 97.0f / 36.0f;
constexpr float KA = 1.0f / (2.0f * WA2 * (WA2 - WB2)), KB = 1.0f / (2.0f * WB2 * (WB2 - WA2));

struct Maps { CUtensorMap c, x, xf, w1, w2, w2f, wc, o1, o2; };

__device__ __align__(1024) unsigned char g_V[6 * V_POS];
__device__ __align__(1024) unsigned char g_U[6 * 8 * 16 * UB];
__device__ __align__(1024) float4 g_X[128 * 16 * 256];
__device__ unsigned int g_flagV[132];
__device__ unsigned int g_flagU[128];
__device__ unsigned int g_flagB[256];
__device__ unsigned int g_flagX[256];
__device__ unsigned int g_done;
#define TL(i)

__device__ __forceinline__ uint32_t smem_u32(const void* p) { return (uint32_t)__cvta_generic_to_shared(p); }
__device__ __forceinline__ void mbar_init(uint32_t bar, uint32_t cnt) { asm volatile("mbarrier.init.shared::cta.b64 [%0], %1;" ::"r"(bar), "r"(cnt)); }
__device__ __forceinline__ void mbar_expect_tx(uint32_t bar, uint32_t bytes) { asm volatile("mbarrier.arrive.expect_tx.shared::cta.b64 _, [%0], %1;" ::"r"(bar), "r"(bytes) : "memory"); }
__device__ __forceinline__ void mbar_arrive(uint32_t bar) { asm volatile("mbarrier.arrive.shared::cta.b64 _, [%0];" ::"r"(bar) : "memory"); }
__device__ __forceinline__ void mbar_wait(uint32_t bar) {
  uint32_t done;
  int iters = 0;
  do {
    asm volatile("{\n.reg .pred p;\nmbarrier.try_wait.parity.shared::cta.b64 p, [%1], 0;\nselp.u32 %0, 1, 0, p;\n}" : "=r"(done) : "r"(bar) : "memory");
  } while (!done && ++iters < (1 << 20));
}
__device__ __forceinline__ void bulk_g2s(uint32_t dst, const void* src, uint32_t bytes, uint32_t bar) {
  asm volatile("cp.async.bulk.shared::cluster.global.mbarrier::complete_tx::bytes [%0], [%1], %2, [%3];" ::"r"(dst), "l"(src), "r"(bytes), "r"(bar) : "memory");
}
__device__ __forceinline__ void tma3(uint32_t dst, const CUtensorMap* m, int c0, int c1, int c2, uint32_t bar) {
  asm volatile("cp.async.bulk.tensor.3d.shared::cluster.global.mbarrier::complete_tx::bytes [%0], [%1, {%3, %4, %5}], [%2];"
               ::"r"(dst), "l"(m), "r"(bar), "r"(c0), "r"(c1), "r"(c2) : "memory");
}
__device__ __forceinline__ void tma3_hint(uint32_t dst, const CUtensorMap* m, int c0, int c1, int c2, uint32_t bar, uint64_t pol) {
  asm volatile("cp.async.bulk.tensor.3d.shared::cluster.global.mbarrier::complete_tx::bytes.L2::cache_hint [%0], [%1, {%3, %4, %5}], [%2], %6;"
               ::"r"(dst), "l"(m), "r"(bar), "r"(c0), "r"(c1), "r"(c2), "l"(pol) : "memory");
}
__device__ __forceinline__ void tma3_store(const CUtensorMap* m, uint32_t src, int c0, int c1, int c2) {
  asm volatile("cp.async.bulk.tensor.3d.global.shared::cta.bulk_group [%0, {%2, %3, %4}], [%1];" ::"l"(m), "r"(src), "r"(c0), "r"(c1), "r"(c2) : "memory");
}
__device__ __forceinline__ void l2_prefetch(const void* p, uint32_t bytes) { asm volatile("cp.async.bulk.prefetch.L2.global [%0], %1;" ::"l"(p), "r"(bytes) : "memory"); }
__device__ __forceinline__ void l2_prefetch_hint(const void* p, uint32_t bytes, uint64_t pol) { asm volatile("cp.async.bulk.prefetch.L2.global.L2::cache_hint [%0], %1, %2;" ::"l"(p), "r"(bytes), "l"(pol) : "memory"); }
__device__ __forceinline__ void bulk_commit() { asm volatile("cp.async.bulk.commit_group;" ::: "memory"); }
__device__ __forceinline__ void bulk_wait0() { asm volatile("cp.async.bulk.wait_group 0;" ::: "memory"); }
__device__ __forceinline__ void fence_async_smem() { asm volatile("fence.proxy.async.shared::cta;" ::: "memory"); }
__device__ __forceinline__ void fence_async_all() { asm volatile("fence.proxy.async;" ::: "memory"); }
__device__ __forceinline__ void flag_set(unsigned int* f) {
  asm volatile("fence.acq_rel.gpu;\nst.relaxed.gpu.global.u32 [%0], 1;" ::"l"(f) : "memory");
}
__device__ __forceinline__ void flag_wait(const unsigned int* f) {
  uint32_t v;
  int iters = 0;
  do {
    asm volatile("ld.acquire.gpu.global.u32 %0, [%1];" : "=r"(v) : "l"(f) : "memory");
  } while (v == 0 && ++iters < (1 << 20));
}
__device__ __forceinline__ void wg_fence() { asm volatile("wgmma.fence.sync.aligned;" ::: "memory"); }
__device__ __forceinline__ void wg_commit() { asm volatile("wgmma.commit_group.sync.aligned;" ::: "memory"); }
template <int N> __device__ __forceinline__ void wg_wait() { asm volatile("wgmma.wait_group.sync.aligned %0;" ::"n"(N) : "memory"); }
template <int N> __device__ __forceinline__ void fence_regs(float (&d)[N]) {
#pragma unroll
  for (int i = 0; i < N; i++) asm volatile("" : "+f"(d[i])::"memory");
}
__device__ __forceinline__ void ldsm4(uint32_t a, uint32_t (&r)[4]) {
  asm volatile("ldmatrix.sync.aligned.m8n8.x4.shared.b16 {%0,%1,%2,%3}, [%4];" : "=r"(r[0]), "=r"(r[1]), "=r"(r[2]), "=r"(r[3]) : "r"(a) : "memory");
}
__device__ __forceinline__ void ldsm4t(uint32_t a, uint32_t (&r)[4]) {
  asm volatile("ldmatrix.sync.aligned.m8n8.x4.trans.shared.b16 {%0,%1,%2,%3}, [%4];" : "=r"(r[0]), "=r"(r[1]), "=r"(r[2]), "=r"(r[3]) : "r"(a) : "memory");
}
__device__ __forceinline__ void stsm4(uint32_t a, uint32_t r0, uint32_t r1, uint32_t r2, uint32_t r3) {
  asm volatile("stmatrix.sync.aligned.m8n8.x4.shared.b16 [%0], {%1,%2,%3,%4};" ::"r"(a), "r"(r0), "r"(r1), "r"(r2), "r"(r3) : "memory");
}
__device__ __forceinline__ void stsm4t(uint32_t a, uint32_t r0, uint32_t r1, uint32_t r2, uint32_t r3) {
  asm volatile("stmatrix.sync.aligned.m8n8.x4.trans.shared.b16 [%0], {%1,%2,%3,%4};" ::"r"(a), "r"(r0), "r"(r1), "r"(r2), "r"(r3) : "memory");
}
__device__ __forceinline__ uint32_t pack2(float lo, float hi) {
  uint32_t r;
  asm("cvt.rn.bf16x2.f32 %0, %1, %2;" : "=r"(r) : "f"(hi), "f"(lo));
  return r;
}
__device__ __forceinline__ float bf_lo(uint32_t v) { return __uint_as_float(v << 16); }
__device__ __forceinline__ float bf_hi(uint32_t v) { return __uint_as_float(v & 0xffff0000u); }

#define R8(b) "+f"(d[b]), "+f"(d[b+1]), "+f"(d[b+2]), "+f"(d[b+3]), "+f"(d[b+4]), "+f"(d[b+5]), "+f"(d[b+6]), "+f"(d[b+7])
__device__ __forceinline__ void wgmma_n256_tb(float (&d)[128], uint64_t da, uint64_t db, int sd) {
  asm volatile("{\n.reg .pred p;\nsetp.ne.b32 p, %130, 0;\n"
    "wgmma.mma_async.sync.aligned.m64n256k16.f32.bf16.bf16 "
    "{%0,%1,%2,%3,%4,%5,%6,%7,%8,%9,%10,%11,%12,%13,%14,%15,%16,%17,%18,%19,%20,%21,%22,%23,"
    "%24,%25,%26,%27,%28,%29,%30,%31,%32,%33,%34,%35,%36,%37,%38,%39,%40,%41,%42,%43,%44,%45,%46,%47,"
    "%48,%49,%50,%51,%52,%53,%54,%55,%56,%57,%58,%59,%60,%61,%62,%63,%64,%65,%66,%67,%68,%69,%70,%71,"
    "%72,%73,%74,%75,%76,%77,%78,%79,%80,%81,%82,%83,%84,%85,%86,%87,%88,%89,%90,%91,%92,%93,%94,%95,"
    "%96,%97,%98,%99,%100,%101,%102,%103,%104,%105,%106,%107,%108,%109,%110,%111,%112,%113,%114,%115,%116,%117,%118,%119,"
    "%120,%121,%122,%123,%124,%125,%126,%127},"
    "%128, %129, p, 1, 1, 0, 1;\n}"
    : R8(0),R8(8),R8(16),R8(24),R8(32),R8(40),R8(48),R8(56),R8(64),R8(72),R8(80),R8(88),R8(96),R8(104),R8(112),R8(120)
    : "l"(da), "l"(db), "r"(sd));
}
__device__ __forceinline__ void wgmma_n144_ta(float (&d)[72], uint64_t da, uint64_t db, int sd) {
  asm volatile("{\n.reg .pred p;\nsetp.ne.b32 p, %74, 0;\n"
    "wgmma.mma_async.sync.aligned.m64n144k16.f32.bf16.bf16 "
    "{%0,%1,%2,%3,%4,%5,%6,%7,%8,%9,%10,%11,%12,%13,%14,%15,%16,%17,%18,%19,%20,%21,%22,%23,"
    "%24,%25,%26,%27,%28,%29,%30,%31,%32,%33,%34,%35,%36,%37,%38,%39,%40,%41,%42,%43,%44,%45,%46,%47,"
    "%48,%49,%50,%51,%52,%53,%54,%55,%56,%57,%58,%59,%60,%61,%62,%63,%64,%65,%66,%67,%68,%69,%70,%71},"
    "%72, %73, p, 1, 1, 1, 0;\n}"
    : R8(0),R8(8),R8(16),R8(24),R8(32),R8(40),R8(48),R8(56),R8(64)
    : "l"(da), "l"(db), "r"(sd));
}
__device__ __forceinline__ void wgmma_n128(float (&d)[64], uint64_t da, uint64_t db, int sd) {
  asm volatile("{\n.reg .pred p;\nsetp.ne.b32 p, %66, 0;\n"
    "wgmma.mma_async.sync.aligned.m64n128k16.f32.bf16.bf16 "
    "{%0,%1,%2,%3,%4,%5,%6,%7,%8,%9,%10,%11,%12,%13,%14,%15,%16,%17,%18,%19,%20,%21,%22,%23,"
    "%24,%25,%26,%27,%28,%29,%30,%31,%32,%33,%34,%35,%36,%37,%38,%39,%40,%41,%42,%43,%44,%45,%46,%47,"
    "%48,%49,%50,%51,%52,%53,%54,%55,%56,%57,%58,%59,%60,%61,%62,%63},"
    "%64, %65, p, 1, 1, 0, 0;\n}"
    : R8(0),R8(8),R8(16),R8(24),R8(32),R8(40),R8(48),R8(56)
    : "l"(da), "l"(db), "r"(sd));
}

constexpr uint64_t DESC_K128 = ((uint64_t)1 << 62) | ((uint64_t)64 << 32) | ((uint64_t)1 << 16);
constexpr uint64_t DESC_MN128 = ((uint64_t)1 << 62) | ((uint64_t)64 << 32) | ((uint64_t)512 << 16);
constexpr uint64_t DESC_K64 = ((uint64_t)2 << 62) | ((uint64_t)32 << 32) | ((uint64_t)1 << 16);
constexpr uint64_t DESC_K0 = ((uint64_t)8 << 32) | ((uint64_t)64 << 16);

__device__ __forceinline__ int seqA(int i) { return i + min(max(i - LEAD + 1, 0), 18); }
__device__ __forceinline__ int seqB(int j) { return LEAD + 2 * j; }

__device__ __forceinline__ void act8(uint32_t addr, float sa, float sb, float (&o)[8]) {
  uint32_t r[4];
  asm volatile("ld.shared.v4.u32 {%0,%1,%2,%3}, [%4];" : "=r"(r[0]), "=r"(r[1]), "=r"(r[2]), "=r"(r[3]) : "r"(addr) : "memory");
#pragma unroll
  for (int i = 0; i < 8; i++) {
    float t = fmaf((i & 1) ? bf_hi(r[i >> 1]) : bf_lo(r[i >> 1]), sa, sb);
    float th;
    asm("tanh.approx.f32 %0, %1;" : "=f"(th) : "f"(t));
    o[i] = fmaf(t, th, t);
  }
}
__device__ __forceinline__ void st8(unsigned char* p, const float (&v)[8]) {
  asm volatile("st.global.v4.u32 [%0], {%1,%2,%3,%4};" ::"l"(p), "r"(pack2(v[0], v[1])), "r"(pack2(v[2], v[3])), "r"(pack2(v[4], v[5])), "r"(pack2(v[6], v[7])) : "memory");
}

__device__ __forceinline__ void main_unit(float (&d)[64], uint32_t sb, uint32_t bars, int m, int wg, int sd) {
  const int s = seqA(18 + m);
  mbar_wait(bars + 8 * (B_FULL + s));
  const uint32_t va = sb + (s % NSLOT) * SLOT + wg * 8192, ua = sb + (s % NSLOT) * SLOT + VB;
  wg_fence();
#pragma unroll
  for (int k = 0; k < 2; k++)
#pragma unroll
    for (int t = 0; t < 3; t++)
      wgmma_n128(d, DESC_K0 | (uint64_t)((ua + (k * 3 + t) * 2048) >> 4), DESC_K64 | (uint64_t)((va + t * 1024 + k * 32) >> 4), (k | t) ? 1 : sd);
  wg_commit();
  wg_wait<1>();
  if (m > 0 && (threadIdx.x & 31) == 0) mbar_arrive(bars + 8 * (B_EMPTY + seqA(17 + m)));
}

__global__ void __launch_bounds__(384, 1)
controlnet_kernel(const __grid_constant__ Maps maps, const unsigned char* __restrict__ gx, const unsigned char* __restrict__ gxf,
                  const unsigned char* __restrict__ gw1, const unsigned char* __restrict__ gwc) {
  extern __shared__ __align__(1024) unsigned char smem[];
  const uint32_t sb = smem_u32(smem);
  const uint32_t bars = sb + OFF_BAR;
  const int tid = threadIdx.x, lane = tid & 31;
  const int wg = __shfl_sync(0xffffffff, tid >> 7, 0);
  const int warp = __shfl_sync(0xffffffff, (tid >> 5) & 3, 0);
  const int bid = blockIdx.x;
  const int dp = bid & 3, cr = bid >> 2;
  const int rg = bid & 7, phalf = (bid >> 3) & 1, chg = bid >> 4;
  const int partner = bid ^ 8;

  if (tid < NBAR) {
    int cnt = 1;
    if (tid >= B_EMPTY && tid < B_FFULL) {
      const int s = tid - B_EMPTY;
      cnt = 4;
      if (s == seqA(17) || s == seqB(17)) cnt = 1;
      else if (s >= seqA(18) && !(s < LEAD + 36 && ((s - LEAD) & 1) == 0)) cnt = 8;
    } else if (tid >= B_FEMPTY && tid < B_CFULL) cnt = 8;
    else if (tid >= B_HIN && tid < B_BASE) cnt = 4;
    else if (tid == B_UDONE || tid == B_VDONE) cnt = 8;
    else if (tid >= B_XDONE && tid < B_XRDY) cnt = 4;
    mbar_init(bars + 8 * tid, cnt);
    asm volatile("fence.mbarrier_init.release.cluster;" ::: "memory");
  }
  __syncthreads();

  if (wg == 2) {
    asm volatile("setmaxnreg.dec.sync.aligned.u32 40;");
    if (warp == 0) {
      if (lane == 0) {
        uint64_t pol;
        asm volatile("createpolicy.fractional.L2::evict_first.b64 %0, 1.0;" : "=l"(pol));
        for (int k = 0; k < 8; k++) {
          if (k == 4)
            for (int q = 0; q < 8; q++) {
              mbar_expect_tx(bars + 8 * (B_CFULL + q), 8192);
              tma3_hint(sb + OFF_A + q * 8192, &maps.c, 0, bid * 64, q, bars + 8 * (B_CFULL + q), pol);
            }
          if (k >= 4) mbar_wait(bars + 8 * (B_FEMPTY + k - 4));
          const uint32_t fb = bars + 8 * (B_FFULL + k), dst = sb + (k & 3) * FSLOT;
          mbar_expect_tx(fb, FSLOT);
          for (int g = 0; g < 3; g++) {
            const int G = cr * 3 + g;
            tma3_hint(dst + 16384 + g * 6144, &maps.wc, k * 64, (G & 31) * 16, (G >> 5) * 3, fb, pol);
          }
          tma3(dst, &maps.w2f, 0, k * 64, dp * 2, fb);
        }
        TL(0);
        const unsigned char* Vb = g_V + ((rg >> 2) * 66 + (rg & 3) * 16) * 1024;
        for (int s = 0; s < NSEQ; s++) {
          if (s < NSLOT) mbar_wait(bars + 8 * (B_FEMPTY + min(4 + s, 7)));
          else mbar_wait(bars + 8 * (B_EMPTY + s - NSLOT));
          int w = 0, i;
          if (s < LEAD) i = s;
          else if (s < LEAD + 36) { const int t = s - LEAD; if (t & 1) i = LEAD + (t >> 1); else { w = 1; i = t >> 1; } }
          else i = s - 18;
          const uint32_t fb = bars + 8 * (B_FULL + s), dst = sb + (s % NSLOT) * SLOT;
          if (i < 18) {
            mbar_expect_tx(fb, SLOT);
            if (i < 8) tma3(dst, &maps.w1, 0, i * 64, w * 4, fb);
            else if (i == 8) tma3_hint(dst, &maps.x, 0, bid * 64, w * 4, fb, pol);
            else if (i < 17) tma3(dst, &maps.w2, 0, (i - 9) * 64, w * 4, fb);
            else tma3_hint(dst, &maps.xf, 0, bid * 64, w * 4, fb, pol);
          } else {
            const int m = i - 18;
            if (m == 0) { TL(1); mbar_wait(bars + 8 * B_VU); fence_async_all(); TL(2); }
            int kc, pos;
            if (m < 32) { kc = m >> 1; pos = 1 + 2 * phalf + (m & 1); } else { kc = m - 32; pos = 5 * phalf; }
            mbar_expect_tx(fb, VB + UB);
            bulk_g2s(dst, Vb + pos * V_POS + kc * V_KC, VB, fb);
            bulk_g2s(dst + VB, g_U + ((pos * 8 + chg) * 16 + kc) * UB, UB, fb);
          }
        }
      }
    } else if (warp == 1) {
      if (lane == 0) {
        mbar_wait(bars + 8 * B_UDONE);
        flag_set(&g_flagU[bid]);
        mbar_wait(bars + 8 * B_VDONE);
        flag_set(&g_flagV[(bid >> 6) * 66 + (bid & 63) + 1]);
      }
      __syncwarp();
      if (lane < 2) {
        mbar_wait(bars + 8 * (B_XDONE + lane));
        flag_set(&g_flagX[bid * 2 + lane]);
        flag_wait(&g_flagX[partner * 2 + lane]);
        g_flagX[partner * 2 + lane] = 0;
        mbar_arrive(bars + 8 * (B_XRDY + lane));
      }
    } else if (warp == 2) {
      if (lane == 0) {
        for (int w = 0; w < 2; w++) {
          const int s = w ? seqB(17) : seqA(17);
          mbar_wait(bars + 8 * (B_STAGED + w));
          tma3_store(&maps.o1, sb + (s % NSLOT) * SLOT, 0, bid * 64, w * 4);
          bulk_commit();
          bulk_wait0();
          mbar_arrive(bars + 8 * (B_EMPTY + s));
          fence_async_all();
          flag_set(&g_flagB[bid * 2 + w]);
        }
      }
      __syncwarp();
      if (lane < 16) flag_wait(&g_flagB[(rg * 16 + lane) * 2 + (chg >> 2)]);
      __syncwarp();
      if (lane == 0) {
        fence_async_all();
        for (int w = 0; w < 2; w++) {
          mbar_expect_tx(bars + 8 * (B_BASE + w), 32768);
          tma3(sb + OFF_A + w * 32768, &maps.o2, chg * 64, 2 - phalf, rg * 256 + w * 128, bars + 8 * (B_BASE + w));
          tma3(sb + OFF_A + w * 32768 + 16384, &maps.o2, chg * 64, 3 * phalf, rg * 256 + w * 128, bars + 8 * (B_BASE + w));
        }
        mbar_wait(bars + 8 * B_VU);
        __threadfence();
        if (atomicAdd(&g_done, 1) == 127) {
          for (int i = 0; i < 132; i++) g_flagV[i] = 0;
          for (int i = 0; i < 128; i++) g_flagU[i] = 0;
          for (int i = 0; i < 256; i++) g_flagB[i] = 0;
          g_done = 0;
        }
      }
    } else {
      uint64_t pol;
      asm volatile("createpolicy.fractional.L2::evict_first.b64 %0, 1.0;" : "=l"(pol));
      if (dp == 0) {
        for (int r = lane; r < 144; r += 32) {
          const int G = cr * 3 + r / 48, dj = (r % 48) >> 4, c = (G & 31) * 16 + (r & 15);
          l2_prefetch_hint(gwc + (size_t)((((G >> 5) * 3 + dj) * 512 + c) * 1024 + 512), 512, pol);
        }
      }
      if (lane == 0) l2_prefetch(gw1 + bid * 4096, 4096);
      const int y = bid & 63;
      if (y == 0 || y == 63) {
        const int prow = (bid >> 6) * 66 + (y ? 65 : 0);
        for (int i = 0; i < 96; i++) {
          uint4* p = (uint4*)(g_V + (size_t)i * V_KC + prow * 1024);
          p[lane] = make_uint4(0, 0, 0, 0);
          p[lane + 32] = make_uint4(0, 0, 0, 0);
        }
        __syncwarp();
        if (lane == 0) flag_set(&g_flagV[prow]);
      }
      mbar_wait(bars + 8 * (B_FEMPTY + 1));
      if (lane < 4) l2_prefetch_hint(gx + (size_t)bid * 65536 + lane * 16384, 16384, pol);
      mbar_wait(bars + 8 * (B_EMPTY + 2));
      if (lane < 4) l2_prefetch_hint(gxf + (size_t)bid * 65536 + lane * 16384, 16384, pol);
      mbar_wait(bars + 8 * B_UDONE);
      flag_wait(&g_flagU[lane * 4 + (chg >> 1)]);
      mbar_wait(bars + 8 * B_VDONE);
      if (lane < 18) flag_wait(&g_flagV[(rg >> 2) * 66 + (rg & 3) * 16 + lane]);
      __syncwarp();
      if (lane == 0) mbar_arrive(bars + 8 * B_VU);
    }
  } else {
    asm volatile("setmaxnreg.inc.sync.aligned.u32 232;");
    const int g = lane >> 2, q = lane & 3;
    float acc[128];
    {
      float fa[72];
#pragma unroll 1
      for (int k = 0; k < 8; k++) {
        mbar_wait(bars + 8 * (B_FFULL + k));
        if (k == 0) TL(0);
        const uint32_t aa = sb + (k & 3) * FSLOT + wg * 8192, bb = sb + (k & 3) * FSLOT + 16384;
        wg_fence();
#pragma unroll
        for (int ks = 0; ks < 4; ks++)
          wgmma_n144_ta(fa, DESC_MN128 | (uint64_t)((aa + ks * 2048) >> 4), DESC_K128 | (uint64_t)((bb + ks * 32) >> 4), (k | ks) != 0);
        wg_commit();
        wg_wait<1>();
        if (k > 0 && lane == 0) mbar_arrive(bars + 8 * (B_FEMPTY + k - 1));
      }
      wg_wait<0>();
      fence_regs(fa);
      if (lane == 0) mbar_arrive(bars + 8 * (B_FEMPTY + 7));
      TL(1);
      {
        const int s = wg ? seqB(0) : seqA(0);
        mbar_wait(bars + 8 * (B_CFULL + 0));
        mbar_wait(bars + 8 * (B_FULL + s));
        const uint32_t aa = sb + OFF_A, bb = sb + (s % NSLOT) * SLOT;
        wg_fence();
#pragma unroll
        for (int ks = 0; ks < 4; ks++)
          wgmma_n256_tb(acc, DESC_K128 | (uint64_t)((aa + ks * 32) >> 4), DESC_MN128 | (uint64_t)((bb + ks * 2048) >> 4), ks != 0);
        wg_commit();
#pragma unroll
        for (int gi = 0; gi < 3; gi++) {
          const int G = cr * 3 + gi;
          unsigned char* up = g_U + (((dp * 2 + wg) * 32 + (G & 31)) * 3 + (G >> 5)) * 2048 + (warp * 16 + g) * 16 + q * 4;
#pragma unroll
          for (int h = 0; h < 2; h++)
#pragma unroll
            for (int r = 0; r < 2; r++) {
              float u[6][2];
#pragma unroll
              for (int e = 0; e < 2; e++) {
                const float w0 = fa[4 * (6 * gi + h) + 2 * r + e], w1 = fa[4 * (6 * gi + 2 + h) + 2 * r + e], w2 = fa[4 * (6 * gi + 4 + h) + 2 * r + e];
                const float ea = fmaf(w2, WA2 * KA, w0 * KA), eb = fmaf(w2, WB2 * KB, w0 * KB);
                u[0][e] = w0; u[5][e] = w2;
                u[1][e] = fmaf(w1, WA * KA, ea); u[2][e] = fmaf(w1, -WA * KA, ea);
                u[3][e] = fmaf(w1, WB * KB, eb); u[4][e] = fmaf(w1, -WB * KB, eb);
              }
#pragma unroll
              for (int p = 0; p < 6; p++)
                asm volatile("st.global.u32 [%0], %1;" ::"l"(up + p * (8 * 16 * UB) + h * 1024 + r * 128), "r"(pack2(u[p][0], u[p][1])) : "memory");
            }
        }
        __syncwarp();
        if (lane == 0) mbar_arrive(bars + 8 * B_UDONE);
        TL(2);
        wg_wait<0>();
        if (lane == 0) mbar_arrive(bars + 8 * (B_EMPTY + s));
      }
    }
#pragma unroll 1
    for (int k = 1; k < 8; k++) {
      const int s = wg ? seqB(k) : seqA(k);
      mbar_wait(bars + 8 * (B_CFULL + k));
      mbar_wait(bars + 8 * (B_FULL + s));
      const uint32_t aa = sb + OFF_A + k * 8192, bb = sb + (s % NSLOT) * SLOT;
      wg_fence();
#pragma unroll
      for (int ks = 0; ks < 4; ks++)
        wgmma_n256_tb(acc, DESC_K128 | (uint64_t)((aa + ks * 32) >> 4), DESC_MN128 | (uint64_t)((bb + ks * 2048) >> 4), 1);
      wg_commit();
      wg_wait<0>();
      if (lane == 0) mbar_arrive(bars + 8 * (B_EMPTY + s));
    }
    fence_regs(acc);
    TL(3);
    const uint32_t frow = warp * 16 + (lane & 7) + ((lane >> 3) & 1) * 8;
    const uint32_t foff = frow * 128, fx = (lane >> 4) ^ (lane & 7);
    {
      const int s = wg ? seqB(8) : seqA(8);
      mbar_wait(bars + 8 * (B_FULL + s));
      mbar_wait(bars + 8 * (B_EMPTY + (wg ? seqA(7) : seqB(3))));
      const uint32_t xs = sb + (s % NSLOT) * SLOT + foff, hs = sb + OFF_A + wg * 32768 + foff;
      float s0 = 0.f, s1 = 0.f, q0 = 0.f, q1 = 0.f;
#pragma unroll
      for (int j = 0; j < 32; j += 2) {
        const uint32_t off = (j >> 3) * 8192 + ((fx ^ (j & 7)) << 4);
        uint32_t r[4];
        ldsm4(xs + off, r);
        float v[8];
#pragma unroll
        for (int i = 0; i < 4; i++) {
          v[2 * i] = acc[4 * j + 2 * i] + bf_lo(r[i]);
          v[2 * i + 1] = acc[4 * j + 2 * i + 1] + bf_hi(r[i]);
        }
        s0 += (v[0] + v[1]) + (v[4] + v[5]);
        s1 += (v[2] + v[3]) + (v[6] + v[7]);
        q0 = fmaf(v[0], v[0], fmaf(v[1], v[1], fmaf(v[4], v[4], fmaf(v[5], v[5], q0))));
        q1 = fmaf(v[2], v[2], fmaf(v[3], v[3], fmaf(v[6], v[6], fmaf(v[7], v[7], q1))));
        stsm4(hs + off, pack2(v[0], v[1]), pack2(v[2], v[3]), pack2(v[4], v[5]), pack2(v[6], v[7]));
      }
#pragma unroll
      for (int o = 1; o < 4; o <<= 1) {
        s0 += __shfl_xor_sync(0xffffffff, s0, o); s1 += __shfl_xor_sync(0xffffffff, s1, o);
        q0 += __shfl_xor_sync(0xffffffff, q0, o); q1 += __shfl_xor_sync(0xffffffff, q1, o);
      }
      if (q < 2) {
        const uint32_t a = sb + OFF_STATS + (warp * 16 + g + q * 8) * 16 + wg * 8;
        asm volatile("st.shared.v2.f32 [%0], {%1,%2};" ::"r"(a), "f"(q ? s1 : s0), "f"(q ? q1 : q0) : "memory");
      }
      fence_async_smem();
      __syncwarp();
      if (lane == 0) { mbar_arrive(bars + 8 * (B_HIN + wg)); mbar_arrive(bars + 8 * (B_EMPTY + s)); }
    }
    TL(4);
    {
      const int k0 = wg ? 0 : LEAD;
      float d0[8], d1[8], sa = 0.f, sbv = 0.f;
      const uint32_t hl = sb + OFF_A + wg * 32768 + (lane >> 3) * 8192;
      unsigned char* vp = g_V + (wg * 8 + (lane >> 2)) * V_KC + ((bid >> 6) * 66 + (bid & 63) + 1) * 1024;
      mbar_wait(bars + 8 * (B_HIN + 0));
#pragma unroll 1
      for (int k = 0; k < 8; k++) {
        const int s = wg ? seqB(9 + k) : seqA(9 + k);
        if (k == k0) mbar_wait(bars + 8 * (B_HIN + 1));
        mbar_wait(bars + 8 * (B_FULL + s));
        const uint32_t aa = sb + OFF_A + k * 8192, bb = sb + (s % NSLOT) * SLOT;
        wg_fence();
#pragma unroll
        for (int ks = 0; ks < 4; ks++)
          wgmma_n256_tb(acc, DESC_K128 | (uint64_t)((aa + ks * 32) >> 4), DESC_MN128 | (uint64_t)((bb + ks * 2048) >> 4), (k | ks) != 0);
        wg_commit();
        const int t = k - k0;
        if (t >= 0 && t < 4) {
          if (t == 0) {
            const int px = warp * 16 - 1 + lane;
            if (lane < 18 && px >= 0 && px < 64) {
              float4 st;
              asm volatile("ld.shared.v4.f32 {%0,%1,%2,%3}, [%4];" : "=f"(st.x), "=f"(st.y), "=f"(st.z), "=f"(st.w) : "r"(sb + OFF_STATS + px * 16) : "memory");
              const float mean = (st.x + st.z) * (1.0f / 512.0f);
              const float var = fmaxf(fmaf(-mean, mean, (st.y + st.w) * (1.0f / 512.0f)), 0.f);
              sa = 0.5f * rsqrtf(var + 1e-5f);
              sbv = -mean * sa;
            }
            const int p0 = max(warp * 16 - 1, 0), p1 = warp * 16;
            act8(hl + p0 * 128 + (((lane ^ p0) & 7) << 4), __shfl_sync(0xffffffff, sa, 0), __shfl_sync(0xffffffff, sbv, 0), d0);
            act8(hl + p1 * 128 + (((lane ^ p1) & 7) << 4), __shfl_sync(0xffffffff, sa, 1), __shfl_sync(0xffffffff, sbv, 1), d1);
          }
          float d2[8], d3[8], d4[8], d5[8], o[8];
          const int pb = warp * 16 + 4 * t + 1, lb = 4 * t + 2;
          const int p5 = min(pb + 3, 63);
          act8(hl + pb * 128 + (((lane ^ pb) & 7) << 4), __shfl_sync(0xffffffff, sa, lb), __shfl_sync(0xffffffff, sbv, lb), d2);
          act8(hl + (pb + 1) * 128 + (((lane ^ (pb + 1)) & 7) << 4), __shfl_sync(0xffffffff, sa, lb + 1), __shfl_sync(0xffffffff, sbv, lb + 1), d3);
          act8(hl + (pb + 2) * 128 + (((lane ^ (pb + 2)) & 7) << 4), __shfl_sync(0xffffffff, sa, lb + 2), __shfl_sync(0xffffffff, sbv, lb + 2), d4);
          act8(hl + p5 * 128 + (((lane ^ p5) & 7) << 4), __shfl_sync(0xffffffff, sa, lb + 3), __shfl_sync(0xffffffff, sbv, lb + 3), d5);
          const int tx = warp * 4 + t;
          unsigned char* vt = vp + tx * 64 + (((lane ^ (tx >> 1)) & 3) << 4);
#pragma unroll
          for (int i = 0; i < 8; i++) o[i] = fmaf(d2[i], -WS, d0[i]) + d4[i];
          st8(vt, o);
#pragma unroll
          for (int i = 0; i < 8; i++) o[i] = fmaf(d3[i], -WS, d1[i]) + d5[i];
          st8(vt + 5 * V_POS, o);
          float o2[8];
#pragma unroll
          for (int i = 0; i < 8; i++) {
            const float e = fmaf(d2[i], -WB2, d4[i]), od = fmaf(d1[i], -WB2, d3[i]);
            o[i] = fmaf(od, WA, e); o2[i] = fmaf(od, -WA, e);
          }
          st8(vt + 1 * V_POS, o); st8(vt + 2 * V_POS, o2);
#pragma unroll
          for (int i = 0; i < 8; i++) {
            const float e = fmaf(d2[i], -WA2, d4[i]), od = fmaf(d1[i], -WA2, d3[i]);
            o[i] = fmaf(od, WB, e); o2[i] = fmaf(od, -WB, e);
          }
          st8(vt + 3 * V_POS, o); st8(vt + 4 * V_POS, o2);
#pragma unroll
          for (int i = 0; i < 8; i++) { d0[i] = d4[i]; d1[i] = d5[i]; }
          if (t == 3) {
            __syncwarp();
            if (lane == 0) mbar_arrive(bars + 8 * B_VDONE);
            TL(5);
          }
        }
        wg_wait<0>();
        if (lane == 0) mbar_arrive(bars + 8 * (B_EMPTY + s));
      }
    }
    fence_regs(acc);
    TL(6);
    {
      const int s = wg ? seqB(17) : seqA(17);
      mbar_wait(bars + 8 * (B_FULL + s));
      const uint32_t xs = sb + (s % NSLOT) * SLOT + foff;
#pragma unroll
      for (int j = 0; j < 32; j += 2) {
        const uint32_t off = (j >> 3) * 8192 + ((fx ^ (j & 7)) << 4);
        uint32_t r[4];
        ldsm4(xs + off, r);
#pragma unroll
        for (int i = 0; i < 4; i++) r[i] = pack2(acc[4 * j + 2 * i] + bf_lo(r[i]), acc[4 * j + 2 * i + 1] + bf_hi(r[i]));
        stsm4(xs + off, r[0], r[1], r[2], r[3]);
      }
      fence_async_smem();
      __syncwarp();
      if (lane == 0) mbar_arrive(bars + 8 * (B_STAGED + wg));
    }
    TL(7);
    float m1[64], m2[64], m0[64];
#pragma unroll 1
    for (int kc = 0; kc < 16; kc++) {
      main_unit(m1, sb, bars, 2 * kc, wg, kc != 0);
      if (kc == 0) TL(8);
      main_unit(m2, sb, bars, 2 * kc + 1, wg, kc != 0);
    }
    TL(9);
    main_unit(m0, sb, bars, 32, wg, 0);
    fence_regs(m1);
    fence_regs(m2);
    {
      const float sg = phalf ? -1.f : 1.f;
      float4* xo = g_X + bid * 4096 + tid;
#pragma unroll
      for (int i = 0; i < 16; i++) {
        float o[4];
#pragma unroll
        for (int e = 0; e < 4; e++) {
          const float a = m1[4 * i + e], b = m2[4 * i + e];
          m1[4 * i + e] = fmaf(b, sg, a);
          o[e] = fmaf(b, -sg, a);
        }
        asm volatile("st.global.v4.f32 [%0], {%1,%2,%3,%4};" ::"l"(xo + i * 256), "f"(o[0]), "f"(o[1]), "f"(o[2]), "f"(o[3]) : "memory");
      }
      __syncwarp();
      if (lane == 0) mbar_arrive(bars + 8 * (B_XDONE + wg));
    }
#pragma unroll 1
    for (int m = 33; m < 39; m++) main_unit(m0, sb, bars, m, wg, 1);
    TL(10);
    mbar_wait(bars + 8 * (B_XRDY + wg));
    TL(11);
    {
      const float4* xi = g_X + partner * 4096 + tid;
#pragma unroll
      for (int i = 0; i < 16; i++)
        asm volatile("ld.global.cg.v4.f32 {%0,%1,%2,%3}, [%4];" : "=f"(m2[4 * i]), "=f"(m2[4 * i + 1]), "=f"(m2[4 * i + 2]), "=f"(m2[4 * i + 3]) : "l"(xi + i * 256) : "memory");
    }
#pragma unroll 1
    for (int m = 39; m < 42; m++) main_unit(m0, sb, bars, m, wg, 1);
    const uint32_t toff = ((lane >> 4) * 8 + (lane & 7)) * 128 + (((warp * 2 + ((lane >> 3) & 1)) ^ (lane & 7)) << 4);
    const uint32_t tmid = sb + OFF_A + wg * 32768 + toff, tend = tmid + 16384;
    {
      const float c1 = phalf ? WB : WA2, c2 = phalf ? WA : WB2, c3 = phalf ? WB * WB2 : 1.f, c4 = phalf ? WA * WA2 : 1.f;
      mbar_wait(bars + 8 * (B_BASE + wg));
#pragma unroll
      for (int j = 0; j < 16; j += 2) {
        uint32_t r[4], r2[4];
        ldsm4t(tmid + j * 1024, r);
        ldsm4t(tend + j * 1024, r2);
#pragma unroll
        for (int i = 0; i < 4; i++) {
          const float k0v = m1[4 * j + 2 * i], k1v = m1[4 * j + 2 * i + 1], r0v = m2[4 * j + 2 * i], r1v = m2[4 * j + 2 * i + 1];
          r[i] = pack2(fmaf(k0v, c1, fmaf(r0v, c2, bf_lo(r[i]))), fmaf(k1v, c1, fmaf(r1v, c2, bf_hi(r[i]))));
          m1[4 * j + 2 * i] = fmaf(k0v, c3, fmaf(r0v, c4, bf_lo(r2[i])));
          m1[4 * j + 2 * i + 1] = fmaf(k1v, c3, fmaf(r1v, c4, bf_hi(r2[i])));
        }
        stsm4t(tmid + j * 1024, r[0], r[1], r[2], r[3]);
      }
      fence_async_smem();
      asm volatile("bar.sync %0, 128;" ::"r"(wg + 1) : "memory");
      if ((tid & 127) == 0) { tma3_store(&maps.o2, sb + OFF_A + wg * 32768, chg * 64, 2 - phalf, rg * 256 + wg * 128); bulk_commit(); }
    }
    TL(12);
#pragma unroll 1
    for (int m = 42; m < 48; m++) main_unit(m0, sb, bars, m, wg, 1);
    wg_wait<0>();
    fence_regs(m0);
    TL(13);
#pragma unroll
    for (int j = 0; j < 16; j += 2)
      stsm4t(tend + j * 1024, pack2(m0[4 * j] + m1[4 * j], m0[4 * j + 1] + m1[4 * j + 1]), pack2(m0[4 * j + 2] + m1[4 * j + 2], m0[4 * j + 3] + m1[4 * j + 3]),
             pack2(m0[4 * j + 4] + m1[4 * j + 4], m0[4 * j + 5] + m1[4 * j + 5]), pack2(m0[4 * j + 6] + m1[4 * j + 6], m0[4 * j + 7] + m1[4 * j + 7]));
    fence_async_smem();
    asm volatile("bar.sync %0, 128;" ::"r"(wg + 1) : "memory");
    if ((tid & 127) == 0) {
      tma3_store(&maps.o2, sb + OFF_A + wg * 32768 + 16384, chg * 64, 3 * phalf, rg * 256 + wg * 128);
      bulk_commit();
      bulk_wait0();
    }
    TL(14);
  }
}

typedef CUresult (*EncodeFn)(CUtensorMap*, CUtensorMapDataType, cuuint32_t, void*, const cuuint64_t*, const cuuint64_t*, const cuuint32_t*,
                             const cuuint32_t*, CUtensorMapInterleave, CUtensorMapSwizzle, CUtensorMapL2promotion, CUtensorMapFloatOOBfill);

void make_map(EncodeFn enc, CUtensorMap* m, const void* p, uint64_t d0, uint64_t d1, uint64_t d2, uint64_t s1, uint64_t s2, uint32_t b0, uint32_t b1, uint32_t b2) {
  cuuint64_t dims[3] = {d0, d1, d2}, strides[2] = {s1, s2};
  cuuint32_t box[3] = {b0, b1, b2}, es[3] = {1, 1, 1};
  enc(m, CU_TENSOR_MAP_DATA_TYPE_BFLOAT16, 3, const_cast<void*>(p), dims, strides, box, es, CU_TENSOR_MAP_INTERLEAVE_NONE,
      CU_TENSOR_MAP_SWIZZLE_128B, CU_TENSOR_MAP_L2_PROMOTION_L2_256B, CU_TENSOR_MAP_FLOAT_OOB_FILL_NONE);
}

}

extern "C" void kernel_launch(void* const* d_in, const int* in_sizes, int n_in, void* d_out, int out_size) {
  (void)in_sizes; (void)n_in; (void)out_size;
  const void *xf = d_in[0], *x = d_in[1], *c = d_in[2], *w1 = d_in[3], *w2 = d_in[4], *wc = d_in[5];
  static EncodeFn enc = nullptr;
  if (!enc) {
    cudaDriverEntryPointQueryResult qr;
    void* fn = nullptr;
    cudaGetDriverEntryPoint("cuTensorMapEncodeTiled", &fn, cudaEnableDefault, &qr);
    enc = (EncodeFn)fn;
    cudaFuncSetAttribute(controlnet_kernel, cudaFuncAttributeMaxDynamicSharedMemorySize, SMEM_BYTES);
  }
  Maps maps;
  make_map(enc, &maps.c, c, 64, 8192, 8, 1024, 128, 64, 64, 1);
  make_map(enc, &maps.x, x, 64, 8192, 8, 1024, 128, 64, 64, 4);
  make_map(enc, &maps.xf, xf, 64, 8192, 8, 1024, 128, 64, 64, 4);
  make_map(enc, &maps.w1, w1, 64, 512, 8, 1024, 128, 64, 64, 4);
  make_map(enc, &maps.w2, w2, 64, 512, 8, 1024, 128, 64, 64, 4);
  make_map(enc, &maps.w2f, w2, 64, 512, 8, 1024, 128, 64, 64, 2);
  make_map(enc, &maps.wc, wc, 512, 512, 9, 1024, 512 * 1024, 64, 16, 3);
  make_map(enc, &maps.o1, d_out, 64, 8192, 8, 1024, 128, 64, 64, 4);
  make_map(enc, &maps.o2, d_out, 512, 4, 2048, 1024, 4096, 64, 1, 128);
  cudaLaunchConfig_t cfg = {};
  cfg.gridDim = dim3(128);
  cfg.blockDim = dim3(384);
  cfg.dynamicSmemBytes = SMEM_BYTES;
  cfg.stream = cudaStreamPerThread;
  cudaLaunchAttribute at[1];
  at[0].id = cudaLaunchAttributeCooperative;
  at[0].val.cooperative = 1;
  cfg.attrs = at;
  cfg.numAttrs = 1;
  cudaLaunchKernelEx(&cfg, controlnet_kernel, maps, (const unsigned char*)x, (const unsigned char*)xf, (const unsigned char*)w1, (const unsigned char*)wc);
}
```

```cpp
#include <cuda_runtime.h>
#include <cuda_bf16.h>
#include <cuda.h>
#include <stdint.h>

namespace {

constexpr int SLOT = 32768, FSLOT = 34816;
constexpr int OFF_AP = 3 * SLOT;
constexpr int OFF_AO = 5 * SLOT;
constexpr int OFF_STL = OFF_AO + 65536;
constexpr int OFF_STR = OFF_STL + 1056;
constexpr int OFF_BAR = OFF_STR + 1024;
constexpr int B_FFULL = 0, B_CFULL = 8, B_FULL = 16, B_MFULL = 32, B_BOK = 37, B_PFREE = 38, B_PG2 = 39, B_HP = 40, B_VU = 44,
              B_STR = 49, B_PG = 50, B_HPACK = 51, B_XRDY = 52, END1 = 56,
              B_HIN = 56, B_XUSED = 58, B_XIN = 60, B_BDONE = 63, B_VDONE = 64, END4 = 72,
              B_FEMPTY = 72, B_EMPTY = 80, B_MEMPTY = 96, B_UDONE = 101, B_STAGED = 104, NBAR = 112;
constexpr int SMEM_BYTES = OFF_BAR + NBAR * 8;
static_assert(SMEM_BYTES <= 232448, "smem");
constexpr int X_DT = 540;
constexpr int HP_DT = 600;
constexpr int FSTAG = 5;
constexpr int HOLD = 10;
constexpr int LASTN = 3;
constexpr int XPRE = 8, PF0 = 4, PFC = 2, C_INFLIGHT = 3;
constexpr int BAR_LIMIT = 1 << 15, FLAG_LIMIT = 1 << 17;

constexpr int VB = 18432, UB = 12288;
constexpr int V_KC = 132 * 1024, V_POS = 16 * V_KC;

constexpr float WA = 2.0f / 3.0f, WB = 1.5f, WA2 = 4.0f / 9.0f, WB2 = 2.25f, WS = 97.0f / 36.0f;
constexpr float KA = WA * WA2 / (2.0f * WA2 * (WA2 - WB2)), KB = 1.0f / (2.0f * WB2 * (WB2 - WA2));

struct Maps { CUtensorMap w2f, wc, c, x, w1, w2, o2; };
struct Ptrs { const unsigned char *xf, *w1, *w2, *wc; unsigned char *out, *V, *U; unsigned int* flags; };
constexpr int F_V = 0, F_U = 8 * 32, F_B = 12 * 32, F_DONE = 20 * 32, NFLAGS = 21 * 32;

__device__ __align__(1024) unsigned char g_V[6 * V_POS];
__device__ __align__(1024) unsigned char g_U[6 * 8 * 16 * UB];
__device__ __align__(128) unsigned int g_flags[NFLAGS];

__device__ __forceinline__ uint32_t smem_u32(const void* p) { return (uint32_t)__cvta_generic_to_shared(p); }
__device__ __forceinline__ void mbar_init(uint32_t bar, uint32_t cnt) { asm volatile("mbarrier.init.shared::cta.b64 [%0], %1;" ::"r"(bar), "r"(cnt)); }
__device__ __forceinline__ void mbar_expect_tx(uint32_t bar, uint32_t bytes) { asm volatile("mbarrier.arrive.expect_tx.shared::cta.b64 _, [%0], %1;" ::"r"(bar), "r"(bytes) : "memory"); }
__device__ __forceinline__ void mbar_arrive(uint32_t bar) { asm volatile("mbarrier.arrive.shared::cta.b64 _, [%0];" ::"r"(bar) : "memory"); }
__device__ __forceinline__ void mbar_wait(uint32_t bar, uint32_t parity = 0) {
  uint32_t done;
  int iters = 0;
  do {
    asm volatile("{\n.reg .pred p;\nmbarrier.try_wait.parity.shared::cta.b64 p, [%1], %2;\nselp.u32 %0, 1, 0, p;\n}" : "=r"(done) : "r"(bar), "r"(parity) : "memory");
  } while (!done && ++iters < BAR_LIMIT);
}
__device__ __forceinline__ void mbar_wait_cluster(uint32_t bar) {
  uint32_t done;
  int iters = 0;
  do {
    asm volatile("{\n.reg .pred p;\nmbarrier.try_wait.parity.acquire.cluster.shared::cta.b64 p, [%1], 0;\nselp.u32 %0, 1, 0, p;\n}" : "=r"(done) : "r"(bar) : "memory");
  } while (!done && ++iters < BAR_LIMIT);
}
__device__ __forceinline__ bool mbar_test2(uint32_t b0, uint32_t b1) {
  uint32_t done;
  asm volatile("{\n.reg .pred p, q;\nmbarrier.test_wait.parity.shared::cta.b64 p, [%1], 0;\nmbarrier.test_wait.parity.shared::cta.b64 q, [%2], 0;\n"
               "and.pred p, p, q;\nselp.u32 %0, 1, 0, p;\n}" : "=r"(done) : "r"(b0), "r"(b1) : "memory");
  return done;
}
__device__ __forceinline__ bool mbar_test(uint32_t b, uint32_t parity) {
  uint32_t done;
  asm volatile("{\n.reg .pred p;\nmbarrier.test_wait.parity.shared::cta.b64 p, [%1], %2;\nselp.u32 %0, 1, 0, p;\n}" : "=r"(done) : "r"(b), "r"(parity) : "memory");
  return done;
}
__device__ __forceinline__ uint32_t mapa(uint32_t a, uint32_t rank) {
  uint32_t r;
  asm volatile("mapa.shared::cluster.u32 %0, %1, %2;" : "=r"(r) : "r"(a), "r"(rank));
  return r;
}
__device__ __forceinline__ void mbar_arrive_remote(uint32_t rbar) { asm volatile("mbarrier.arrive.relaxed.cluster.shared::cluster.b64 _, [%0];" ::"r"(rbar) : "memory"); }
__device__ __forceinline__ void bulk_s2r(uint32_t rdst, uint32_t src, uint32_t bytes, uint32_t rbar) {
  asm volatile("cp.async.bulk.shared::cluster.shared::cta.mbarrier::complete_tx::bytes [%0], [%1], %2, [%3];" ::"r"(rdst), "r"(src), "r"(bytes), "r"(rbar) : "memory");
}
__device__ __forceinline__ void tma3_prefetch(const CUtensorMap* m, int c0, int c1, int c2) {
  asm volatile("cp.async.bulk.prefetch.tensor.3d.L2.global [%0, {%1, %2, %3}];" ::"l"(m), "r"(c0), "r"(c1), "r"(c2) : "memory");
}
__device__ __forceinline__ uint32_t flag_read(const unsigned int* f) {
  uint32_t v;
  asm volatile("ld.relaxed.gpu.global.u32 %0, [%1];" : "=r"(v) : "l"(f) : "memory");
  return v;
}
__device__ __forceinline__ void bulk_g2s(uint32_t dst, const void* src, uint32_t bytes, uint32_t bar) {
  asm volatile("cp.async.bulk.shared::cluster.global.mbarrier::complete_tx::bytes [%0], [%1], %2, [%3];" ::"r"(dst), "l"(src), "r"(bytes), "r"(bar) : "memory");
}
__device__ __forceinline__ void tma3(uint32_t dst, const CUtensorMap* m, int c0, int c1, int c2, uint32_t bar) {
  asm volatile("cp.async.bulk.tensor.3d.shared::cluster.global.mbarrier::complete_tx::bytes [%0], [%1, {%3, %4, %5}], [%2];"
               ::"r"(dst), "l"(m), "r"(bar), "r"(c0), "r"(c1), "r"(c2) : "memory");
}
__device__ __forceinline__ void tma3_hint(uint32_t dst, const CUtensorMap* m, int c0, int c1, int c2, uint32_t bar, uint64_t pol) {
  asm volatile("cp.async.bulk.tensor.3d.shared::cluster.global.mbarrier::complete_tx::bytes.L2::cache_hint [%0], [%1, {%3, %4, %5}], [%2], %6;"
               ::"r"(dst), "l"(m), "r"(bar), "r"(c0), "r"(c1), "r"(c2), "l"(pol) : "memory");
}
__device__ __forceinline__ void bulk_commit() { asm volatile("cp.async.bulk.commit_group;" ::: "memory"); }
__device__ __forceinline__ void bulk_wait0() { asm volatile("cp.async.bulk.wait_group 0;" ::: "memory"); }
__device__ __forceinline__ void fence_async_smem() { asm volatile("fence.proxy.async.shared::cta;" ::: "memory"); }
__device__ __forceinline__ void fence_gpu() { asm volatile("fence.proxy.async.global;\nfence.release.gpu;" ::: "memory"); }
__device__ __forceinline__ void flag_add(unsigned int* f) { asm volatile("red.relaxed.gpu.global.add.u32 [%0], 1;" ::"l"(f) : "memory"); }
__device__ __forceinline__ void flag_wait(const unsigned int* f, uint32_t want) {
  int iters = 0;
  while (flag_read(f) < want && ++iters < FLAG_LIMIT) __nanosleep(100);
  asm volatile("fence.acquire.gpu;" ::: "memory");
}
__device__ __forceinline__ void tma3_reduce(const CUtensorMap* m, uint32_t src, int c0, int c1, int c2) {
  asm volatile("cp.reduce.async.bulk.tensor.3d.global.shared::cta.add.bulk_group [%0, {%2, %3, %4}], [%1];" ::"l"(m), "r"(src), "r"(c0), "r"(c1), "r"(c2) : "memory");
}
__device__ __forceinline__ void wg_fence() { asm volatile("wgmma.fence.sync.aligned;" ::: "memory"); }
__device__ __forceinline__ void wg_commit() { asm volatile("wgmma.commit_group.sync.aligned;" ::: "memory"); }
template <int N> __device__ __forceinline__ void wg_wait() { asm volatile("wgmma.wait_group.sync.aligned %0;" ::"n"(N) : "memory"); }
template <int N> __device__ __forceinline__ void fence_regs(float (&d)[N]) {
#pragma unroll
  for (int i = 0; i < N; i++) asm volatile("" : "+f"(d[i])::"memory");
}
__device__ __forceinline__ void ldsm4(uint32_t a, uint32_t (&r)[4]) {
  asm volatile("ldmatrix.sync.aligned.m8n8.x4.shared.b16 {%0,%1,%2,%3}, [%4];" : "=r"(r[0]), "=r"(r[1]), "=r"(r[2]), "=r"(r[3]) : "r"(a) : "memory");
}
__device__ __forceinline__ void stsm4(uint32_t a, uint32_t r0, uint32_t r1, uint32_t r2, uint32_t r3) {
  asm volatile("stmatrix.sync.aligned.m8n8.x4.shared.b16 [%0], {%1,%2,%3,%4};" ::"r"(a), "r"(r0), "r"(r1), "r"(r2), "r"(r3) : "memory");
}
__device__ __forceinline__ void stsm4t(uint32_t a, uint32_t r0, uint32_t r1, uint32_t r2, uint32_t r3) {
  asm volatile("stmatrix.sync.aligned.m8n8.x4.trans.shared.b16 [%0], {%1,%2,%3,%4};" ::"r"(a), "r"(r0), "r"(r1), "r"(r2), "r"(r3) : "memory");
}
__device__ __forceinline__ uint32_t pack2(float lo, float hi) {
  uint32_t r;
  asm("cvt.rn.bf16x2.f32 %0, %1, %2;" : "=r"(r) : "f"(hi), "f"(lo));
  return r;
}
__device__ __forceinline__ float bf_lo(uint32_t v) { return __uint_as_float(v << 16); }
__device__ __forceinline__ float bf_hi(uint32_t v) { return __uint_as_float(v & 0xffff0000u); }

#define R8(c, b) c(d[b]), c(d[b+1]), c(d[b+2]), c(d[b+3]), c(d[b+4]), c(d[b+5]), c(d[b+6]), c(d[b+7])
template <int O> __device__ __forceinline__ void wgmma_n128_tb(float (&d)[128], uint64_t da, uint64_t db) {
  asm volatile("{\n.reg .pred p;\nsetp.ne.b32 p, 1, 0;\n"
    "wgmma.mma_async.sync.aligned.m64n128k16.f32.bf16.bf16 "
    "{%0,%1,%2,%3,%4,%5,%6,%7,%8,%9,%10,%11,%12,%13,%14,%15,%16,%17,%18,%19,%20,%21,%22,%23,"
    "%24,%25,%26,%27,%28,%29,%30,%31,%32,%33,%34,%35,%36,%37,%38,%39,%40,%41,%42,%43,%44,%45,%46,%47,"
    "%48,%49,%50,%51,%52,%53,%54,%55,%56,%57,%58,%59,%60,%61,%62,%63},"
    "%64, %65, p, 1, 1, 0, 1;\n}"
    : R8("+f", O+0),R8("+f", O+8),R8("+f", O+16),R8("+f", O+24),R8("+f", O+32),R8("+f", O+40),R8("+f", O+48),R8("+f", O+56)
    : "l"(da), "l"(db));
}
template <int O> __device__ __forceinline__ void wgmma_n128_tb_first(float (&d)[128], uint64_t da, uint64_t db) {
  asm volatile("{\n.reg .pred p;\nsetp.ne.b32 p, 0, 0;\n"
    "wgmma.mma_async.sync.aligned.m64n128k16.f32.bf16.bf16 "
    "{%0,%1,%2,%3,%4,%5,%6,%7,%8,%9,%10,%11,%12,%13,%14,%15,%16,%17,%18,%19,%20,%21,%22,%23,"
    "%24,%25,%26,%27,%28,%29,%30,%31,%32,%33,%34,%35,%36,%37,%38,%39,%40,%41,%42,%43,%44,%45,%46,%47,"
    "%48,%49,%50,%51,%52,%53,%54,%55,%56,%57,%58,%59,%60,%61,%62,%63},"
    "%64, %65, p, 1, 1, 0, 1;\n}"
    : R8("=f", O+0),R8("=f", O+8),R8("=f", O+16),R8("=f", O+24),R8("=f", O+32),R8("=f", O+40),R8("=f", O+48),R8("=f", O+56)
    : "l"(da), "l"(db));
}
__device__ __forceinline__ void wgmma_n144_ta(float (&d)[72], uint64_t da, uint64_t db) {
  asm volatile("{\n.reg .pred p;\nsetp.ne.b32 p, 1, 0;\n"
    "wgmma.mma_async.sync.aligned.m64n144k16.f32.bf16.bf16 "
    "{%0,%1,%2,%3,%4,%5,%6,%7,%8,%9,%10,%11,%12,%13,%14,%15,%16,%17,%18,%19,%20,%21,%22,%23,"
    "%24,%25,%26,%27,%28,%29,%30,%31,%32,%33,%34,%35,%36,%37,%38,%39,%40,%41,%42,%43,%44,%45,%46,%47,"
    "%48,%49,%50,%51,%52,%53,%54,%55,%56,%57,%58,%59,%60,%61,%62,%63,%64,%65,%66,%67,%68,%69,%70,%71},"
    "%72, %73, p, 1, 1, 1, 0;\n}"
    : R8("+f", 0),R8("+f", 8),R8("+f", 16),R8("+f", 24),R8("+f", 32),R8("+f", 40),R8("+f", 48),R8("+f", 56),R8("+f", 64)
    : "l"(da), "l"(db));
}
__device__ __forceinline__ void wgmma_n144_ta_first(float (&d)[72], uint64_t da, uint64_t db) {
  asm volatile("{\n.reg .pred p;\nsetp.ne.b32 p, 0, 0;\n"
    "wgmma.mma_async.sync.aligned.m64n144k16.f32.bf16.bf16 "
    "{%0,%1,%2,%3,%4,%5,%6,%7,%8,%9,%10,%11,%12,%13,%14,%15,%16,%17,%18,%19,%20,%21,%22,%23,"
    "%24,%25,%26,%27,%28,%29,%30,%31,%32,%33,%34,%35,%36,%37,%38,%39,%40,%41,%42,%43,%44,%45,%46,%47,"
    "%48,%49,%50,%51,%52,%53,%54,%55,%56,%57,%58,%59,%60,%61,%62,%63,%64,%65,%66,%67,%68,%69,%70,%71},"
    "%72, %73, p, 1, 1, 1, 0;\n}"
    : R8("=f", 0),R8("=f", 8),R8("=f", 16),R8("=f", 24),R8("=f", 32),R8("=f", 40),R8("=f", 48),R8("=f", 56),R8("=f", 64)
    : "l"(da), "l"(db));
}
__device__ __forceinline__ void wgmma_n128(float (&d)[64], uint64_t da, uint64_t db) {
  asm volatile("{\n.reg .pred p;\nsetp.ne.b32 p, 1, 0;\n"
    "wgmma.mma_async.sync.aligned.m64n128k16.f32.bf16.bf16 "
    "{%0,%1,%2,%3,%4,%5,%6,%7,%8,%9,%10,%11,%12,%13,%14,%15,%16,%17,%18,%19,%20,%21,%22,%23,"
    "%24,%25,%26,%27,%28,%29,%30,%31,%32,%33,%34,%35,%36,%37,%38,%39,%40,%41,%42,%43,%44,%45,%46,%47,"
    "%48,%49,%50,%51,%52,%53,%54,%55,%56,%57,%58,%59,%60,%61,%62,%63},"
    "%64, %65, p, 1, 1, 0, 0;\n}"
    : R8("+f", 0),R8("+f", 8),R8("+f", 16),R8("+f", 24),R8("+f", 32),R8("+f", 40),R8("+f", 48),R8("+f", 56)
    : "l"(da), "l"(db));
}
__device__ __forceinline__ void wgmma_n128_first(float (&d)[64], uint64_t da, uint64_t db) {
  asm volatile("{\n.reg .pred p;\nsetp.ne.b32 p, 0, 0;\n"
    "wgmma.mma_async.sync.aligned.m64n128k16.f32.bf16.bf16 "
    "{%0,%1,%2,%3,%4,%5,%6,%7,%8,%9,%10,%11,%12,%13,%14,%15,%16,%17,%18,%19,%20,%21,%22,%23,"
    "%24,%25,%26,%27,%28,%29,%30,%31,%32,%33,%34,%35,%36,%37,%38,%39,%40,%41,%42,%43,%44,%45,%46,%47,"
    "%48,%49,%50,%51,%52,%53,%54,%55,%56,%57,%58,%59,%60,%61,%62,%63},"
    "%64, %65, p, 1, 1, 0, 0;\n}"
    : R8("=f", 0),R8("=f", 8),R8("=f", 16),R8("=f", 24),R8("=f", 32),R8("=f", 40),R8("=f", 48),R8("=f", 56)
    : "l"(da), "l"(db));
}

constexpr uint32_t HI_128 = (1u << 30) | 64, HI_64 = (2u << 30) | 32, HI_0 = 8;
constexpr uint32_t LO_K = 1u << 16;
constexpr uint32_t LO_MN = 512u << 16;
constexpr uint32_t LO_K0 = 64u << 16;
__device__ __forceinline__ uint64_t mkdesc(uint32_t lo, uint32_t hi) {
  uint64_t d;
  asm("mov.b64 %0, {%1, %2};" : "=l"(d) : "r"(lo), "r"(hi));
  return d;
}
__device__ __forceinline__ uint32_t opaque(uint32_t v) {
  asm volatile("" : "+r"(v));
  return v;
}
__device__ __forceinline__ uint32_t tid_now() { uint32_t t; asm volatile("mov.u32 %0, %%tid.x;" : "=r"(t)); return t; }
__device__ __forceinline__ void pace(uint32_t& t, uint32_t dt) {
  uint32_t now;
  do { __nanosleep(20); asm volatile("mov.u32 %0, %%clock;" : "=r"(now)); } while (now - t < dt);
  t = now;
}
__device__ __forceinline__ uint32_t work_id(uint32_t b) {
  const uint32_t c = b >> 1, t = c - 36, q = (t * 37) >> 8;
  const uint32_t w = c < 4 ? (4 + c) << 3 : (c < 36 ? c - 4 : (1 + t - 7 * q) | ((4 + q) << 3));
  return (w << 1) | (b & 1);
}

__host__ __device__ constexpr int foff_of(int k) { return (k & 6) == 2 ? 229376 - (k - 1) * FSLOT : ((0x23100023 >> (4 * k)) & 3) * FSLOT; }
__host__ __device__ constexpr int zord(int u) { return (0x37654210 >> (4 * u)) & 7; }
__host__ __device__ constexpr int aoff_of(int kk) { return (kk < 4 ? OFF_AO : OFF_AP) + (kk & 3) * 8192; }
__host__ __device__ constexpr int coff_of(int kk) { return aoff_of(kk < 6 ? kk : kk - 6); }
__host__ __device__ constexpr int kc_of(int e) { return (e & 1) * 8 + (e >> 1); }
__device__ __forceinline__ void granule(int L, int& k16, int& di) { const int o = L / 3; di = L - 3 * o; k16 = kc_of(o >> 1) * 2 + (o & 1); }

__device__ __forceinline__ void turn_wait(int wg) { asm volatile("bar.sync %0, 256;" ::"r"(4 + wg) : "memory"); }
__device__ __forceinline__ void turn_pass(int wg) { asm volatile("bar.arrive %0, 256;" ::"r"(5 - wg) : "memory"); }

template <bool FIRST> __device__ __forceinline__ void gz_issue(float (&acc)[128], uint32_t la, uint32_t lb, int wg) {
  turn_wait(wg);
  wg_fence();
#pragma unroll
  for (int ks = 0; ks < 4; ks++) {
    if (FIRST && ks == 0) {
      wgmma_n128_tb_first<0>(acc, mkdesc(la, HI_128), mkdesc(lb, HI_128));
      wgmma_n128_tb_first<64>(acc, mkdesc(la, HI_128), mkdesc(lb + 1024, HI_128));
    } else {
      wgmma_n128_tb<0>(acc, mkdesc(la + 2 * ks, HI_128), mkdesc(lb + 128 * ks, HI_128));
      wgmma_n128_tb<64>(acc, mkdesc(la + 2 * ks, HI_128), mkdesc(lb + 128 * ks + 1024, HI_128));
    }
  }
  wg_commit();
  turn_pass(wg);
}

__device__ __forceinline__ void load_fold_unit(const Maps& maps, uint32_t dst, uint32_t fb, int k, int dp, int cr) {
  mbar_expect_tx(fb, FSLOT);
  tma3(dst, &maps.w2f, 0, k * 64, dp * 2, fb);
#pragma unroll
  for (int g = 0; g < 3; g++) {
    int k16, di;
    granule(cr + 32 * g, k16, di);
    tma3(dst + 16384 + g * 6144, &maps.wc, k * 64, k16 * 16, di * 3, fb);
  }
}

struct Ring { int i, ph; bool ready; };
template <bool PP, bool FIRST> __device__ __forceinline__ void main_unit(float (&d)[64], uint32_t sdu, uint32_t sdv, uint32_t bars, int m, Ring& r, int wg) {
  if (!r.ready) mbar_wait(bars + 8 * (B_MFULL + r.i), r.ph);
  const uint32_t lu = sdu + r.i * (SLOT >> 4), lv = sdv + r.i * (SLOT >> 4);
  const int ip = r.i ? r.i - 1 : 4;
  if (r.i == 0) r.ph ^= 1;
  if (++r.i == 5) r.i = 0;
  r.ready = mbar_test(bars + 8 * (B_MFULL + r.i), r.ph);
  if (PP) turn_wait(wg);
  wg_fence();
#pragma unroll
  for (int k = 0; k < 2; k++)
#pragma unroll
    for (int t = 0; t < 3; t++) {
      if (FIRST && k == 0 && t == 0) wgmma_n128_first(d, mkdesc(lu, HI_0), mkdesc(lv, HI_64));
      else wgmma_n128(d, mkdesc(lu + (k * 3 + t) * 128, HI_0), mkdesc(lv + t * 64 + k * 2, HI_64));
    }
  wg_commit();
  if (PP || (m == 47 && wg == 0)) turn_pass(wg);
  wg_wait<1>();
  if (m > 0 && (threadIdx.x & 31) == 0) mbar_arrive(bars + 8 * (B_MEMPTY + ip));
}
template <int I0, int I1> __device__ __forceinline__ void xsend(float (&m1)[64], const float (&m2)[64], uint32_t rz, uint32_t rb) {
#pragma unroll
  for (int i = I0; i < I1; i++) {
    float o[4];
#pragma unroll
    for (int e = 0; e < 4; e++) {
      const float a = m1[4 * i + e], b = m2[4 * i + e];
      m1[4 * i + e] = a + b;
      o[e] = a - b;
    }
    asm volatile("st.async.shared::cluster.mbarrier::complete_tx::bytes.v4.f32 [%0], {%1,%2,%3,%4}, [%5];"
                 ::"r"(rz + i * 2048), "f"(o[0]), "f"(o[1]), "f"(o[2]), "f"(o[3]), "r"(rb + (i >> 3) * 8) : "memory");
  }
}
template <int H> __device__ __forceinline__ void xrecv(float (&m2)[64], uint32_t a, uint32_t bar) {
  mbar_wait_cluster(bar + 8 * H);
#pragma unroll
  for (int k = 8 * H; k < 8 * H + 8; k++)
    asm volatile("ld.shared.v4.f32 {%0,%1,%2,%3}, [%4];" : "=f"(m2[4 * k]), "=f"(m2[4 * k + 1]), "=f"(m2[4 * k + 2]), "=f"(m2[4 * k + 3]) : "r"(a + k * 2048) : "memory");
}
template <int U> __device__ __forceinline__ void xmid(float (&m1)[64], const float (&m2)[64], uint32_t tmid) {
#pragma unroll
  for (int v = U * 2; v < U * 2 + 2; v++) {
    uint32_t r[4];
#pragma unroll
    for (int i = 0; i < 4; i++) {
      const float k0v = m1[8 * v + 2 * i], k1v = m1[8 * v + 2 * i + 1], r0v = m2[8 * v + 2 * i], r1v = m2[8 * v + 2 * i + 1];
      r[i] = pack2(WB * fmaf(r0v, WB, k0v), WB * fmaf(r1v, WB, k1v));
      m1[8 * v + 2 * i] = fmaf(k0v, WB * WB2, r0v);
      m1[8 * v + 2 * i + 1] = fmaf(k1v, WB * WB2, r1v);
    }
    stsm4t(tmid + v * 2048, r[0], r[1], r[2], r[3]);
  }
}

__device__ __forceinline__ void act2(uint32_t raw, float a, float b, float& o0, float& o1) {
  const float t0 = fmaf(bf_lo(raw), a, b), t1 = fmaf(bf_hi(raw), a, b);
  float h0, h1;
  asm("tanh.approx.f32 %0, %1;" : "=f"(h0) : "f"(t0));
  asm("tanh.approx.f32 %0, %1;" : "=f"(h1) : "f"(t1));
  o0 = fmaf(t0, h0, t0);
  o1 = fmaf(t1, h1, t1);
}
__device__ __forceinline__ uint32_t lds32(uint32_t a) {
  uint32_t v;
  asm volatile("ld.shared.u32 %0, [%1];" : "=r"(v) : "r"(a) : "memory");
  return v;
}
__device__ __forceinline__ float4 lds128(uint32_t a) {
  float4 v;
  asm volatile("ld.shared.v4.f32 {%0,%1,%2,%3}, [%4];" : "=f"(v.x), "=f"(v.y), "=f"(v.z), "=f"(v.w) : "r"(a) : "memory");
  return v;
}
__device__ __forceinline__ void stg32(unsigned char* p, uint32_t v) { asm volatile("st.global.u32 [%0], %1;" ::"l"(p), "r"(v) : "memory"); }

template <int PC> __device__ __forceinline__ void ef_compute(const float (&fa)[72], uint32_t (&o)[12]) {
  constexpr int gi = PC >> 1, h = PC & 1;
#pragma unroll
  for (int r = 0; r < 2; r++) {
    float u[6][2];
#pragma unroll
    for (int e = 0; e < 2; e++) {
      const float w0 = fa[4 * (6 * gi + h) + 2 * r + e], w1 = fa[4 * (6 * gi + 2 + h) + 2 * r + e], w2 = fa[4 * (6 * gi + 4 + h) + 2 * r + e];
      const float ea = fmaf(w2, WA2 * KA, w0 * KA), eb = fmaf(w2, WB2 * KB, w0 * KB);
      u[0][e] = w0; u[5][e] = w2;
      u[1][e] = fmaf(w1, WA * KA, ea); u[2][e] = fmaf(w1, -WA * KA, ea);
      u[3][e] = fmaf(w1, WB * KB, eb); u[4][e] = fmaf(w1, WB * KB, -eb);
    }
#pragma unroll
    for (int p = 0; p < 6; p++) o[6 * r + p] = opaque(pack2(u[p][0], u[p][1]));
  }
}
__device__ __forceinline__ void ef_store(const uint32_t (&o)[12], unsigned char* up) {
#pragma unroll
  for (int i = 0; i < 12; i++) stg32(up + (i % 6) * (8 * 16 * UB) + (i / 6) * 128, o[i]);
}
#define EF_STORE(pc) do { ef_store(uo[pc], P.U + uoff[(pc) >> 1] + ((pc) & 1) * 1024); \
    if ((pc) & 1) { __syncwarp(); if (lane == 0) mbar_arrive(bars + 8 * (B_UDONE + ((pc) >> 1))); } } while (0)

__global__ void __launch_bounds__(512, 1)
controlnet_kernel(const __grid_constant__ Ptrs P, const __grid_constant__ Maps maps) {
  extern __shared__ __align__(1024) unsigned char smem[];
  const uint32_t sb = smem_u32(smem);
  const uint32_t bars = sb + OFF_BAR;
  const int tid = threadIdx.x, lane = tid & 31;
  const int wid = __shfl_sync(0xffffffff, tid >> 5, 0);
  const int wg = wid >> 2, warp = wid & 3;
  const int bid = work_id(blockIdx.x);
  const int rank = bid & 1, row0 = ((bid >> 1) & 7) * 16 + (bid >> 4) * 2;
  const int dp = ((bid >> 3) & 2) | rank, cr = ((bid >> 1) & 7) | ((bid >> 5) << 3);
  const int rg = (bid >> 1) & 7, chg = bid >> 4;
  const int prow0 = (row0 >> 6) * 66 + (row0 & 63) + 1;
  if (tid < 36 * PF0) {
    const int r = dp * 36 + tid % 36;
    int k16, di;
    granule(cr + 32 * (r / 48), k16, di);
    asm volatile("prefetch.global.L2 [%0];" ::"l"(P.wc + ((di * 3 + ((r % 48) >> 4)) * 512 + k16 * 16 + (r & 15)) * 1024 + (tid / 36) * 128));
  } else if (tid >= 256 && tid < 256 + 4 * PF0) {
    asm volatile("prefetch.global.L2 [%0];" ::"l"(P.w2 + ((tid - 256) >> 2) * 65536 + bid * 512 + (tid & 3) * 128));
  } else if (tid == 320) {
    asm volatile("prefetch.tensormap [%0];" ::"l"(&maps.w2f) : "memory");
    asm volatile("prefetch.tensormap [%0];" ::"l"(&maps.wc) : "memory");
  }
  if (lane == 0) {
    const int ch = wid ^ 7;
    if (ch < NBAR / 8) {
      const uint32_t cnt = ch < END1 / 8 ? 1 : (ch < END4 / 8 ? 4 : 8);
#pragma unroll
      for (int i = 0; i < 8; i++) mbar_init(bars + ch * 64 + 8 * i, cnt);
      asm volatile("fence.mbarrier_init.release.cluster;" ::: "memory");
    }
  }
  __syncwarp();
  asm volatile("barrier.cluster.arrive.relaxed.aligned;" ::: "memory");
  if (wid == 7 && lane == 0) {
    fence_async_smem();
#pragma unroll 1
    for (int k = 0; k < 6; k++) {
      load_fold_unit(maps, sb + foff_of(k), bars + 8 * (B_FFULL + k), k, dp, cr);
    }
  }
  __syncwarp();
  asm volatile("barrier.cluster.wait.aligned;" ::: "memory");

  if (wg == 3) {
    asm volatile("setmaxnreg.dec.sync.aligned.u32 24;");
    if (warp == 0) {
      if (lane == 0) {
#pragma unroll 1
        for (int k = 6; k < 8; k++) {
          mbar_wait(bars + 8 * (B_FEMPTY + k - 6));
          load_fold_unit(maps, sb + foff_of(k), bars + 8 * (B_FFULL + k), k, dp, cr);
        }
        int slot = 0;
#pragma unroll 1
        for (int u = 0; u < 16; u++) {
          mbar_wait(bars + 8 * (u >= 3 ? B_EMPTY + u - 3 : B_FEMPTY + (u == 2 ? 7 : 4 + u)));
          const int kk = u < 8 ? u : zord(u - 8);
          mbar_expect_tx(bars + 8 * (B_FULL + u), SLOT);
          tma3(sb + slot * SLOT, u < 8 ? &maps.w1 : &maps.w2, 0, ((kk + 4 * rank) & 7) * 64, rank * 4, bars + 8 * (B_FULL + u));
          slot = slot == 2 ? 0 : slot + 1;
        }
        const unsigned char* vs = P.V + (((rg >> 2) * 66 + (rg & 3) * 16) * 1024 + (1 + 2 * rank) * V_POS);
        const unsigned char* us = P.U + (chg * 16 + (1 + 2 * rank) * 128) * UB;
        uint32_t wb = bars + 8 * (B_EMPTY + 13), wp = 0;
        int i = 1, ph = 1;
        mbar_wait(bars + 8 * B_VU);
#pragma unroll 1
        for (int m = 1; m <= 48; m++) {
          const uint32_t fb = bars + 8 * (B_MFULL + i), dst = sb + i * SLOT;
          mbar_wait(wb, wp);
          mbar_expect_tx(fb, VB + UB);
          bulk_g2s(dst, vs, VB, fb);
          bulk_g2s(dst + VB, us, UB, fb);
          int dk, dpos = 0;
          if (m < 32) {
            if (m & 1) { dk = 0; dpos = 1; }
            else { dk = (m & 2) ? 8 : -7; dpos = -1; }
            if ((m & 7) == 0 || m == 4) mbar_wait(bars + 8 * (B_VU + 1 + (m >> 3)));
          } else if (m == 32) { dk = -15; dpos = 3 * rank - 2; }
          else dk = 1;
          vs += (dpos * 16 + dk) * V_KC;
          us += (dpos * 128 + dk) * UB;
          if (i == 0) ph ^= 1;
          if (++i == 5) i = 0;
          if (m < 5) wb = bars + 8 * (B_EMPTY + (m == 4 ? 15 : 14));
          else { wb = bars + 8 * (B_MEMPTY + i); wp = ph; }
        }
      }
    } else if (warp == 1) {
      const int y0 = row0 & 63;
      if (lane == 0) {
        asm volatile("prefetch.tensormap [%0];" ::"l"(&maps.c) : "memory");
        asm volatile("prefetch.tensormap [%0];" ::"l"(&maps.w1) : "memory");
        asm volatile("prefetch.tensormap [%0];" ::"l"(&maps.x) : "memory");
        asm volatile("prefetch.tensormap [%0];" ::"l"(&maps.w2) : "memory");
        asm volatile("prefetch.tensormap [%0];" ::"l"(&maps.o2) : "memory");
        mbar_expect_tx(bars + 8 * B_STR, 1024);
#pragma unroll
        for (int j = 0; j < 4; j++) { mbar_expect_tx(bars + 8 * (B_HP + j), 16384); mbar_expect_tx(bars + 8 * (B_XRDY + j), 16384); }
      }
      if ((rg & 3) == 0 || (rg & 3) == 3) {
        unsigned char* zp = P.V + (chg * 2 + rank) * V_KC + ((rg >> 2) * 66 + ((rg & 3) ? 65 : 0)) * 1024 + lane * 16;
        mbar_wait(bars + 8 * (B_FEMPTY + 7));
#pragma unroll 1
        for (int i = 0; i < 6; i++) {
          uint4* p = (uint4*)(zp + i * V_POS);
          p[0] = make_uint4(0, 0, 0, 0);
          p[32] = make_uint4(0, 0, 0, 0);
        }
      }
      __syncwarp();
      if (lane == 0) {
        unsigned int* f0 = P.flags + F_V + rg * 32;
        unsigned int* f1 = ((y0 & 15) == 0 && y0 != 0) ? f0 - 32 : (((y0 & 15) == 14 && y0 != 62) ? f0 + 32 : nullptr);
#pragma unroll 1
        for (int j = -1; j < 5; j++) {
          const int us = j < 0 ? 0 : ((j == 2 || j == 3) ? j - 1 : -1);
          if (us >= 0) mbar_wait(bars + 8 * (B_UDONE + us));
          if (j >= 0) mbar_wait(bars + 8 * (B_VDONE + (j < 2 ? j : 2 * j - 1)));
          fence_gpu();
          if (j >= 0) {
            flag_add(f0 + j);
            if (f1) flag_add(f1 + j);
          }
          if (us >= 0) flag_add(P.flags + F_U + dp * 32 + us);
        }
      }
    } else if (warp == 2) {
      if (lane == 0) {
        uint64_t pol;
        asm volatile("createpolicy.fractional.L2::evict_first.b64 %0, 1.0;" : "=l"(pol));
        uint32_t tp = 0;
#pragma unroll 1
        for (int j = 0; j < 4; j++) {
          mbar_wait(bars + 8 * (j < 2 ? B_FEMPTY + 7 : B_EMPTY + j));
          if (j < 2) mbar_wait(bars + 8 * (B_CFULL + 1 + j));
          const uint32_t xd = sb + aoff_of(j < 2 ? 6 + j : j);
          pace(tp, j ? X_DT : 0);
          mbar_expect_tx(bars + 8 * B_XIN, 8192);
          mbar_expect_tx(bars + 8 * (B_XIN + 1), 8192);
          tma3_hint(xd, &maps.x, 0, row0 * 64, rank * 4 + j, bars + 8 * B_XIN, pol);
          pace(tp, X_DT);
          tma3_hint(xd + 32768, &maps.x, 0, row0 * 64 + 64, rank * 4 + j, bars + 8 * (B_XIN + 1), pol);
        }
        mbar_wait(bars + 8 * (B_EMPTY + 5));
        mbar_arrive_remote(mapa(bars + 8 * B_PG, rank ^ 1));
        {
          const uint32_t rap = mapa(sb + OFF_AP, rank ^ 1), rhp = mapa(bars + 8 * B_HP, rank ^ 1);
          mbar_wait_cluster(bars + 8 * B_PG);
          mbar_wait(bars + 8 * (B_HIN + 0));
          mbar_wait(bars + 8 * (B_HIN + 1));
          mbar_arrive_remote(mapa(bars + 8 * B_PG2, rank ^ 1));
          pace(tp, 0);
#pragma unroll 1
          for (int j = 0; j < 4; j++) {
            if (j) pace(tp, HP_DT);
            if (j == 2) mbar_wait_cluster(bars + 8 * B_PG2);
            bulk_s2r(rap + j * 8192, sb + OFF_AO + j * 8192, 8192, rhp + 8 * j);
            pace(tp, HP_DT);
            bulk_s2r(rap + 32768 + j * 8192, sb + OFF_AO + 32768 + j * 8192, 8192, rhp + 8 * j);
          }
#pragma unroll 1
          for (int j = 0; j < 4; j++) mbar_wait_cluster(bars + 8 * (B_HP + j));
          mbar_arrive_remote(mapa(bars + 8 * B_HPACK, rank ^ 1));
        }
        mbar_wait(bars + 8 * B_BDONE);
        mbar_arrive_remote(mapa(bars + 8 * B_PFREE, rank ^ 1));
        fence_gpu();
        flag_add(P.flags + F_B + rg * 32);
        flag_wait(P.flags + F_B + rg * 32, 16);
        mbar_arrive(bars + 8 * B_BOK);
        mbar_wait(bars + 8 * (B_VU + 4));
      }
      __syncwarp();
      unsigned int prev = 0;
      if (lane == 0) prev = atomicAdd(P.flags + F_DONE, 1);
      if (__shfl_sync(0xffffffff, prev, 0) == 127) {
#pragma unroll 1
        for (int i = lane; i < NFLAGS; i += 32) P.flags[i] = 0;
      }
    } else {
      {
        const int r = dp * 36 + lane, r2 = r + 32;
        int k16, di, k16b, dib;
        granule(cr + 32 * (r / 48), k16, di);
        granule(cr + 32 * (r2 / 48), k16b, dib);
        const unsigned char* p = P.wc + ((di * 3 + ((r % 48) >> 4)) * 512 + k16 * 16 + (r & 15)) * 1024 + 768;
        const unsigned char* p2 = P.wc + ((dib * 3 + ((r2 % 48) >> 4)) * 512 + k16b * 16 + (r2 & 15)) * 1024 + 768;
        if (lane >= 4) p2 = P.w2 + 393216 + bid * 1024 + (lane & 3) * 256;
        asm volatile("prefetch.global.L2 [%0];" ::"l"(p));
        asm volatile("prefetch.global.L2 [%0];" ::"l"(p + 128));
        if (lane < 8) {
          asm volatile("prefetch.global.L2 [%0];" ::"l"(p2));
          asm volatile("prefetch.global.L2 [%0];" ::"l"(p2 + 128));
        }
        asm volatile("prefetch.global.L2 [%0];" ::"l"(P.w1 + bid * 4096 + lane * 128));
      }
      if (lane == 0) {
        uint64_t pol;
        asm volatile("createpolicy.fractional.L2::evict_first.b64 %0, 1.0;" : "=l"(pol));
        mbar_wait(bars + 8 * B_FEMPTY);
#pragma unroll 1
        for (int kk = 0; kk < PFC; kk++) {
          tma3_prefetch(&maps.c, 0, row0 * 64, kk + 4 * rank);
          tma3_prefetch(&maps.c, 0, row0 * 64 + 64, kk + 4 * rank);
          __nanosleep(300);
        }
        mbar_wait(bars + 8 * (B_FEMPTY + 3));
#pragma unroll 1
        for (int kk = 0; kk < 8; kk++) {
          if (kk >= C_INFLIGHT) mbar_wait(bars + 8 * (B_CFULL + min(kk - C_INFLIGHT, 3)));
          if (kk >= 4) mbar_wait(bars + 8 * (kk == 4 ? B_FEMPTY + 7 : B_EMPTY + kk - 5));
          const uint32_t cb = bars + 8 * (B_CFULL + kk), dst = sb + coff_of(kk);
          mbar_expect_tx(cb, 16384);
          if (kk < 4) {
            tma3(dst, &maps.c, 0, row0 * 64, (kk + 4 * rank) & 7, cb);
            tma3(dst + 32768, &maps.c, 0, row0 * 64 + 64, (kk + 4 * rank) & 7, cb);
          } else {
            tma3_hint(dst, &maps.c, 0, row0 * 64, (kk + 4 * rank) & 7, cb, pol);
            tma3_hint(dst + 32768, &maps.c, 0, row0 * 64 + 64, (kk + 4 * rank) & 7, cb, pol);
          }
        }
        const uint32_t want = ((rg & 3) == 0 || (rg & 3) == 3) ? 18 : 20;
#pragma unroll 1
        for (int j = 0; j < 5; j++) {
          if (j == 0) {
            mbar_wait(bars + 8 * B_HIN);
            flag_wait(P.flags + F_U + (chg >> 1) * 32, 32);
          }
          mbar_wait(bars + 8 * (B_VDONE + (j < 2 ? j : 2 * j - 1)));
          flag_wait(P.flags + F_V + rg * 32 + j, want);
          if (j == 2 || j == 3) flag_wait(P.flags + F_U + (chg >> 1) * 32 + j - 1, 32);
          mbar_arrive(bars + 8 * (B_VU + j));
        }
      }
    }
  } else if (wg == 2) {
    asm volatile("setmaxnreg.dec.sync.aligned.u32 40;");
    mbar_wait(bars + 8 * (B_HIN + 0));
    mbar_wait(bars + 8 * (B_HIN + 1));
    mbar_wait_cluster(bars + 8 * B_STR);
    {
      const int t = tid & 127;
      const uint32_t a = sb + OFF_STL + ((t >> 6) * 66 + (t & 63) + 1) * 8;
      float s0, q0, s1, q1;
      asm volatile("ld.shared.v2.f32 {%0,%1}, [%2];" : "=f"(s0), "=f"(q0) : "r"(a) : "memory");
      asm volatile("ld.shared.v2.f32 {%0,%1}, [%2];" : "=f"(s1), "=f"(q1) : "r"(sb + OFF_STR + t * 8) : "memory");
      const float mean = (s0 + s1) * (1.0f / 512.0f);
      const float var = fmaxf(fmaf(-mean, mean, (q0 + q1) * (1.0f / 512.0f)), 0.f);
      const float r = 0.5f * rsqrtf(var + 1e-5f);
      asm volatile("st.shared.v2.f32 [%0], {%1,%2};" ::"r"(a), "f"(r), "f"(-mean * r) : "memory");
      if (t < 4) asm volatile("st.shared.v2.f32 [%0], {%1,%1};" ::"r"(sb + OFF_STL + ((t >> 1) * 66 + (t & 1) * 65) * 8), "f"(0.f) : "memory");
    }
    asm volatile("bar.sync 3, 128;" ::: "memory");
    uint32_t hp, ap, vo;
    {
      const uint32_t tn = tid_now(), wq = (tn >> 5) & 3;
      const uint32_t w = (tn >> 4) & 1;
      hp = sb + OFF_AO + w * 32768 + wq * 2048 + (tn & 15) * 4;
      ap = sb + OFF_STL + w * 528 + wq * 128;
      vo = rank * 8 * V_KC + (prow0 + w) * 1024 + wq * 256 + (((tn * 4) ^ (wq * 32)) & 63) + 2 * V_POS;
    }
    const uint32_t first = warp ? (uint32_t)-128 : 896u, last = warp == 3 ? 0u : 2048u;
#pragma unroll 1
    for (int pc = 0; pc < 8; pc++) {
      float d0x, d0y, d1x, d1y;
      uint32_t r2, r3, r4, r5;
      float4 ab, ac;
      {
        const uint32_t r0 = lds32((hp ^ 0x70) + first), r1 = lds32(hp);
        const float4 aa = lds128(ap);
        r2 = lds32((hp ^ 0x10) + 128); r4 = lds32((hp ^ 0x30) + 384);
        ab = lds128(ap + 16); ac = lds128(ap + 32);
        r3 = lds32((hp ^ 0x20) + 256); r5 = lds32((hp ^ 0x40) + 512);
        act2(r0, aa.x, aa.y, d0x, d0y);
        act2(r1, aa.z, aa.w, d1x, d1y);
      }
#pragma unroll
      for (int t = 0; t < 4; t++) {
        float d2x, d2y, d3x, d3y, d4x, d4y, d5x, d5y;
        act2(r2, ab.x, ab.y, d2x, d2y);
        act2(r4, ac.x, ac.y, d4x, d4y);
        act2(r3, ab.z, ab.w, d3x, d3y);
        act2(r5, ac.z, ac.w, d5x, d5y);
        if (t < 3) {
          const int p = 4 * t + 4;
          r2 = lds32((hp ^ (((p + 1) & 7) << 4)) + (p + 1) * 128); r4 = lds32((hp ^ (((p + 3) & 7) << 4)) + (p + 3) * 128);
          r3 = lds32((hp ^ (((p + 2) & 7) << 4)) + (p + 2) * 128);
          r5 = t < 2 ? lds32((hp ^ (((p + 4) & 7) << 4)) + (p + 4) * 128) : lds32(hp + last);
        }
        unsigned char* vt = P.V + ((vo ^ ((t >> 1) << 4)) + t * 64);
        stg32(vt - 2 * V_POS, pack2(fmaf(d2x, -WS, d0x) + d4x, fmaf(d2y, -WS, d0y) + d4y));
        {
          const float ex = fmaf(d2x, -WB2, d4x), ey = fmaf(d2y, -WB2, d4y), ox = fmaf(d1x, -WB2, d3x), oy = fmaf(d1y, -WB2, d3y);
          stg32(vt - V_POS, pack2(fmaf(ox, WA, ex), fmaf(oy, WA, ey)));
          stg32(vt, pack2(fmaf(ox, -WA, ex), fmaf(oy, -WA, ey)));
        }
        stg32(vt + 3 * V_POS, pack2(fmaf(d3x, -WS, d1x) + d5x, fmaf(d3y, -WS, d1y) + d5y));
        const float ex = fmaf(d2x, -WA2, d4x), ey = fmaf(d2y, -WA2, d4y), ox = fmaf(d1x, -WA2, d3x), oy = fmaf(d1y, -WA2, d3y);
        if (t < 3) { ab = lds128(ap + 48 + 32 * t); ac = lds128(ap + 64 + 32 * t); }
        stg32(vt + V_POS, pack2(fmaf(ox, WB, ex), fmaf(oy, WB, ey)));
        stg32(vt + 2 * V_POS, pack2(fmaf(ox, -WB, ex), fmaf(oy, -WB, ey)));
        d0x = d4x; d0y = d4y; d1x = d5x; d1y = d5y;
      }
      __syncwarp();
      if (lane == 0) mbar_arrive(bars + 8 * (B_VDONE + pc));
      if (pc == 0) { hp += 64; vo += V_KC; }
      else if (pc == 1) {
        const uint32_t w = (tid_now() >> 4) & 1;
        hp += 8192 - 64 - w * (32768 - 64); ap -= w * 528; vo += V_KC + w * (V_KC - 1024);
      }
      else if (pc & 1) { hp -= 32768 - 8192; ap -= 528; vo += 2 * V_KC - 1024; }
      else { hp += 32768; ap += 528; vo += 1024; }
    }
    {
      const uint32_t t = tid_now() & 127;
      const uint32_t so = (t >> 3) * 128 + (((t ^ (t >> 3)) & 7) << 4);
      const uint32_t go = row0 * 65536 + rank * 512 + (t >> 3) * 1024 + (t & 7) * 16;
      uint64_t pol;
      asm volatile("createpolicy.fractional.L2::evict_first.b64 %0, 1.0;" : "=l"(pol));
#pragma unroll 1
      for (int i = 0; i < 8; i++) {
        const uint32_t g = go + (i & 1) * 65536 + (i >> 1) * 128;
        const uint32_t sa = sb + OFF_AO + (i & 1) * 32768 + (i >> 1) * 8192 + so;
        uint32_t f[4][4];
#pragma unroll
        for (int k = 0; k < 4; k++)
          asm volatile("ld.global.nc.L1::no_allocate.L2::cache_hint.v4.u32 {%0,%1,%2,%3}, [%4], %5;"
                       : "=r"(f[k][0]), "=r"(f[k][1]), "=r"(f[k][2]), "=r"(f[k][3]) : "l"(P.xf + g + k * 16384), "l"(pol) : "memory");
        if (i == 0) mbar_wait(bars + 8 * B_STAGED);
        if (i == 6) mbar_wait(bars + 8 * (B_STAGED + 1));
#pragma unroll
        for (int k = 0; k < 4; k++) {
          uint32_t z[4];
          asm volatile("ld.shared.v4.u32 {%0,%1,%2,%3}, [%4];" : "=r"(z[0]), "=r"(z[1]), "=r"(z[2]), "=r"(z[3]) : "r"(sa + k * 2048) : "memory");
#pragma unroll
          for (int e = 0; e < 4; e++) asm("add.rn.bf16x2 %0, %0, %1;" : "+r"(z[e]) : "r"(f[k][e]));
          asm volatile("st.global.v4.u32 [%0], {%1,%2,%3,%4};" ::"l"(P.out + g + k * 16384), "r"(z[0]), "r"(z[1]), "r"(z[2]), "r"(z[3]) : "memory");
        }
        if (i == 7) {
          __syncwarp();
          if (lane == 0) mbar_arrive(bars + 8 * B_BDONE);
        }
      }
      mbar_wait(bars + 8 * B_BOK);
      unsigned char* gp = P.out + (uint32_t)((rg * 256 + (t >> 3)) * 4096 + (2 - rank) * 1024 + chg * 128 + (t & 7) * 16);
#pragma unroll 1
      for (int i = 0; i < 4; i++) {
        uint32_t f[4][4];
#pragma unroll
        for (int k = 0; k < 4; k++)
          asm volatile("ld.global.cg.v4.u32 {%0,%1,%2,%3}, [%4];" : "=r"(f[k][0]), "=r"(f[k][1]), "=r"(f[k][2]), "=r"(f[k][3]) : "l"(gp + k * 65536) : "memory");
        mbar_wait(bars + 8 * (B_XUSED + (i >> 1)));
        const uint32_t sa = sb + OFF_AO + (i >> 1) * 32768 + (i & 1) * 8192 + so;
#pragma unroll
        for (int k = 0; k < 4; k++) {
          uint32_t z[4];
          asm volatile("ld.shared.v4.u32 {%0,%1,%2,%3}, [%4];" : "=r"(z[0]), "=r"(z[1]), "=r"(z[2]), "=r"(z[3]) : "r"(sa + k * 2048) : "memory");
#pragma unroll
          for (int e = 0; e < 4; e++) asm("add.rn.bf16x2 %0, %0, %1;" : "+r"(z[e]) : "r"(f[k][e]));
          asm volatile("st.global.v4.u32 [%0], {%1,%2,%3,%4};" ::"l"(gp + k * 65536), "r"(z[0]), "r"(z[1]), "r"(z[2]), "r"(z[3]) : "memory");
        }
        gp += 4 * 65536;
      }
    }
  } else {
    asm volatile("setmaxnreg.inc.sync.aligned.u32 224;");
    const int g = lane >> 2, q = lane & 3;
    const uint32_t sd = (sb & 0x3ffff) >> 4;
    const uint32_t sda = sd + wg * 2048 + LO_K, sdb = sd + LO_MN;
    const uint32_t foff = wg * 32768 + (warp * 16 + (lane & 7) + ((lane >> 3) & 1) * 8) * 128, fx = (lane >> 4) ^ (lane & 7);
    float acc[128];
    uint32_t uo[6][12], uoff[3];
#pragma unroll
    for (int gi = 0; gi < 3; gi++) {
      int k16, di;
      granule(cr + 32 * gi, k16, di);
      uoff[gi] = opaque((dp * 2 + wg) * 16 * UB + (k16 * 3 + di) * 2048 + warp * 256 + lane * 4);
    }
    {
      uint32_t xr[16][4];
      const uint32_t hs = sb + OFF_AO + foff;
      {
        float fa[72];
        if (wg) turn_pass(wg);
        {
          const uint32_t lb = sd + (foff_of(0) >> 4) + 1024 + LO_K, la = lb - 1024 + wg * 512;
          mbar_wait(bars + 8 * B_FFULL);
          wg_fence();
          wgmma_n144_ta_first(fa, mkdesc(la, HI_128), mkdesc(lb, HI_128));
#pragma unroll
          for (int ks = 1; ks < 4; ks++) wgmma_n144_ta(fa, mkdesc(la + ks * 128, HI_128), mkdesc(lb + ks * 2, HI_128));
          wg_commit();
        }
#pragma unroll 1
        for (int k = 1; k < 8; k++) {
          if (k == FSTAG && wg) {
            wg_wait<0>();
            if (lane == 0) mbar_arrive(bars + 8 * (B_FEMPTY + k - 1));
            asm volatile("bar.sync 6, 256;" ::: "memory");
          }
          mbar_wait(bars + 8 * (B_FFULL + k));
          const uint32_t lb = sd + (foff_of(k) >> 4) + 1024 + LO_K, la = lb - 1024 + wg * 512;
          wg_fence();
#pragma unroll
          for (int ks = 0; ks < 4; ks++) wgmma_n144_ta(fa, mkdesc(la + ks * 128, HI_128), mkdesc(lb + ks * 2, HI_128));
          wg_commit();
          if (k == 7 && !wg) asm volatile("bar.arrive 6, 256;" ::: "memory");
          wg_wait<1>();
          if (lane == 0 && !(k == FSTAG && wg)) mbar_arrive(bars + 8 * (B_FEMPTY + k - 1));
        }
        wg_wait<0>();
        if (lane == 0) mbar_arrive(bars + 8 * (B_FEMPTY + 7));
        fence_regs(fa);
        ef_compute<0>(fa, uo[0]); ef_compute<1>(fa, uo[1]); ef_compute<2>(fa, uo[2]);
        ef_compute<3>(fa, uo[3]); ef_compute<4>(fa, uo[4]); ef_compute<5>(fa, uo[5]);
        mbar_wait(bars + 8 * B_CFULL);
        mbar_wait(bars + 8 * B_FULL);
        gz_issue<true>(acc, sda + (aoff_of(0) >> 4), sdb, wg);
        int slot = 1;
#pragma unroll 1
        for (int k = 1; k < 8; k++) {
          const bool ready = mbar_test2(bars + 8 * (B_CFULL + k), bars + 8 * (B_FULL + k));
          if (k == 5) EF_STORE(0);
          if (k == 6) EF_STORE(1);
          if (k == 7) EF_STORE(2);
          wg_wait<0>();
          if (lane == 0) mbar_arrive(bars + 8 * (B_EMPTY + k - 1));
          if (!ready) {
            mbar_wait(bars + 8 * (B_CFULL + k));
            mbar_wait(bars + 8 * (B_FULL + k));
          }
          gz_issue<false>(acc, sda + (coff_of(k) >> 4), sdb + slot * (SLOT >> 4), wg);
          slot = slot == 2 ? 0 : slot + 1;
        }
        EF_STORE(3);
        mbar_wait(bars + 8 * (B_XIN + wg));
#pragma unroll
        for (int j = 0; j < XPRE; j++) ldsm4(hs - (OFF_AO - OFF_AP - 16384) + (j >> 2) * 8192 + ((fx ^ (2 * j & 7)) << 4), xr[j]);
        wg_wait<0>();
        if (lane == 0) mbar_arrive(bars + 8 * (B_EMPTY + 7));
        asm volatile("bar.sync %0, 128;" ::"r"(wg + 1) : "memory");
      }
      fence_regs(acc);
      float st[4][4];
      uint32_t pk[16][4];
#pragma unroll
      for (int i = 0; i < 16; i++) st[i >> 2][i & 3] = 0.f;
#pragma unroll
      for (int j = 0; j < 16; j++) {
        uint32_t p[4];
#pragma unroll
        for (int i = 0; i < 4; i++) {
          p[i] = pack2(acc[8 * j + 2 * i], acc[8 * j + 2 * i + 1]);
          asm("add.rn.bf16x2 %0, %0, %1;" : "+r"(p[i]) : "r"(xr[j][i]));
        }
        stsm4(hs + (j >> 2) * 8192 + ((fx ^ (2 * j & 7)) << 4), p[0], p[1], p[2], p[3]);
#pragma unroll
        for (int i = 0; i < 4; i++) pk[j][i] = p[i];
        if (j + XPRE < 16) ldsm4(hs - (j + XPRE < 8 ? OFF_AO - OFF_AP - 16384 : 0) + ((j + XPRE) >> 2) * 8192 + ((fx ^ (2 * (j + XPRE) & 7)) << 4), xr[j + XPRE]);
      }
      if (P.flags != nullptr) {
#pragma unroll
        for (int j = 0; j < 16; j++)
#pragma unroll
          for (int hf = 0; hf < 2; hf++) {
            float (&c)[4] = st[2 * hf + (j & 1)];
            asm("mma.sync.aligned.m16n8k16.row.col.f32.bf16.bf16.f32 {%0,%1,%2,%3}, {%4,%6,%5,%6}, {%4,%5}, {%0,%1,%2,%3};"
                : "+f"(c[0]), "+f"(c[1]), "+f"(c[2]), "+f"(c[3]) : "r"(pk[j][hf]), "r"(pk[j][hf + 2]), "r"(0x3f803f80u));
          }
      }
      if (q == (g >> 1)) {
#pragma unroll
        for (int hf = 0; hf < 2; hf++) {
          const float sq = (g & 1) ? st[2 * hf][1] + st[2 * hf + 1][1] : st[2 * hf][0] + st[2 * hf + 1][0];
          const float sm = (g & 1) ? st[2 * hf][3] + st[2 * hf + 1][3] : st[2 * hf][2] + st[2 * hf + 1][2];
          const int row = warp * 16 + g + hf * 8;
          asm volatile("st.shared.v2.f32 [%0], {%1,%2};" ::"r"(sb + OFF_STL + (wg * 66 + row + 1) * 8), "f"(sm), "f"(sq) : "memory");
          asm volatile("st.async.shared::cluster.mbarrier::complete_tx::bytes.v2.f32 [%0], {%1,%2}, [%3];"
                       ::"r"(mapa(sb + OFF_STR + (wg * 64 + row) * 8, rank ^ 1)), "f"(sm), "f"(sq), "r"(mapa(bars + 8 * B_STR, rank ^ 1)) : "memory");
        }
      }
      fence_async_smem();
      __syncwarp();
      if (lane == 0) mbar_arrive(bars + 8 * (B_HIN + wg));
    }
    float m1[64], m2[64], m0[64];
    const uint32_t sdu = sd + (VB >> 4) + LO_K0, sdv = sd + wg * 512 + LO_K;
    Ring ring = {1, 0, false};
    uint32_t late[12][4];
    {
      mbar_wait(bars + 8 * (B_HIN + wg));
      mbar_wait(bars + 8 * (B_FULL + 8));
      gz_issue<true>(acc, sda + (aoff_of(zord(0)) >> 4), sdb + (8 % 3) * (SLOT >> 4), wg);
      int slot = 9 % 3;
#pragma unroll 1
      for (int u = 1; u < 8; u++) {
        const int kk = zord(u);
        const uint32_t hb = bars + 8 * (kk >= 4 ? B_HP + kk - 4 : B_FULL + 8);
        const bool ready = mbar_test2(hb, bars + 8 * (B_FULL + 8 + u));
        if (u == 6) EF_STORE(4);
        if (u == 7) EF_STORE(5);
        wg_wait<0>();
        if (lane == 0) mbar_arrive(bars + 8 * (B_EMPTY + 7 + u));
        if (!ready) {
          mbar_wait(hb);
          mbar_wait(bars + 8 * (B_FULL + 8 + u));
        }
        gz_issue<false>(acc, sda + (aoff_of(kk) >> 4), sdb + slot * (SLOT >> 4), wg);
        slot = slot == 2 ? 0 : slot + 1;
      }
      mbar_wait_cluster(bars + 8 * B_HPACK);
      mbar_wait(bars + 8 * (B_VDONE + 1));
      wg_wait<0>();
      if (lane == 0) mbar_arrive(bars + 8 * (B_EMPTY + 15));
      fence_regs(acc);
#pragma unroll
      for (int j = 0; j < 16; j++) {
        if (j >= 4) {
#pragma unroll
          for (int i = 0; i < 4; i++) late[j - 4][i] = opaque(pack2(acc[8 * j + 2 * i], acc[8 * j + 2 * i + 1]));
        } else {
          stsm4(sb + OFF_AO + foff + ((fx ^ (2 * j)) << 4), pack2(acc[8 * j], acc[8 * j + 1]), pack2(acc[8 * j + 2], acc[8 * j + 3]),
                pack2(acc[8 * j + 4], acc[8 * j + 5]), pack2(acc[8 * j + 6], acc[8 * j + 7]));
        }
      }
    }
    main_unit<true, true>(m1, sdu, sdv, bars, 0, ring, wg);
    main_unit<true, true>(m2, sdu, sdv, bars, 1, ring, wg);
#pragma unroll 1
    for (int m = 2; m < 32; m += 2) {
      main_unit<true, false>(m1, sdu, sdv, bars, m, ring, wg);
      main_unit<true, false>(m2, sdu, sdv, bars, m + 1, ring, wg);
#define STAGE(b) { mbar_wait(bars + 8 * (B_VDONE + 2 * b + 1)); _Pragma("unroll") for (int j = 0; j < 4; j++) \
        stsm4(sb + OFF_AO + foff + b * 8192 + ((fx ^ (2 * j)) << 4), late[4 * b - 4 + j][0], late[4 * b - 4 + j][1], late[4 * b - 4 + j][2], late[4 * b - 4 + j][3]); }
      if (m == 2) STAGE(1)
      if (m == HOLD - 4) { STAGE(2) __syncwarp(); if (lane == 0) mbar_arrive(bars + 8 * B_STAGED); }
      if (m == HOLD) { STAGE(3) __syncwarp(); if (lane == 0) mbar_arrive(bars + 8 * (B_STAGED + 1)); }
    }
    main_unit<true, true>(m0, sdu, sdv, bars, 32, ring, wg);
    fence_regs(m1); fence_regs(m2);
    const uint32_t zone = sb + OFF_AO + wg * 32768;
    {
      const bool always = P.flags != nullptr;
      const uint32_t rz = mapa(zone + (tid & 127) * 16, rank ^ 1), rb = mapa(bars + 8 * (B_XRDY + 2 * wg), rank ^ 1);
      mbar_wait_cluster(bars + 8 * B_PFREE);
#define MU(m) main_unit<true, false>(m0, sdu, sdv, bars, m, ring, wg)
      const uint32_t lz = zone + (tid & 127) * 16, lb = bars + 8 * (B_XRDY + 2 * wg);
      const uint32_t tmid = zone + ((lane >> 4) * 8 + (lane & 7)) * 128 + (((warp * 2 + ((lane >> 3) & 1)) ^ (lane & 7)) << 4);
      if (always) xsend<0, 2>(m1, m2, rz, rb);
      MU(33);
      if (always) xsend<2, 5>(m1, m2, rz, rb);
      MU(34);
      if (always) xsend<5, 8>(m1, m2, rz, rb);
      MU(35);
      if (always) xsend<8, 10>(m1, m2, rz, rb);
      MU(36);
      if (always) xsend<10, 12>(m1, m2, rz, rb);
      xrecv<0>(m2, lz, lb);
      MU(37);
      if (always) xsend<12, 14>(m1, m2, rz, rb);
      asm volatile("bar.sync %0, 128;" ::"r"(wg + 1) : "memory");
      if (always) xmid<0>(m1, m2, tmid);
      MU(38);
      if (always) xsend<14, 16>(m1, m2, rz, rb);
      if (always) xmid<1>(m1, m2, tmid);
      MU(39);
      MU(40);
      xrecv<1>(m2, lz, lb);
      MU(41);
      if (always) { xmid<2>(m1, m2, tmid); xmid<3>(m1, m2, tmid); }
      fence_regs(m1);
      __syncwarp();
      if (lane == 0) mbar_arrive(bars + 8 * (B_XUSED + wg));
#pragma unroll 1
      for (int m = 42; m < 48 - LASTN; m++) MU(m);
      turn_wait(wg);
#pragma unroll 1
      for (int m = 48 - LASTN; m < 48; m++) main_unit<false, false>(m0, sdu, sdv, bars, m, ring, wg);
    }
    const uint32_t tend = sb + OFF_AO + wg * 32768 + 16384 + ((lane >> 4) * 8 + (lane & 7)) * 128 + (((warp * 2 + ((lane >> 3) & 1)) ^ (lane & 7)) << 4);
    mbar_wait(bars + 8 * B_BOK);
    wg_wait<0>();
    fence_regs(m0);
#pragma unroll
    for (int hf = 0; hf < 2; hf++) {
#pragma unroll
      for (int j = 8 * hf; j < 8 * hf + 8; j += 2)
        stsm4t(tend + j * 1024, pack2(m0[4 * j] + m1[4 * j], m0[4 * j + 1] + m1[4 * j + 1]), pack2(m0[4 * j + 2] + m1[4 * j + 2], m0[4 * j + 3] + m1[4 * j + 3]),
               pack2(m0[4 * j + 4] + m1[4 * j + 4], m0[4 * j + 5] + m1[4 * j + 5]), pack2(m0[4 * j + 6] + m1[4 * j + 6], m0[4 * j + 7] + m1[4 * j + 7]));
      fence_async_smem();
      if (warp == 3 * hf) {
        asm volatile("bar.sync %0, 128;" ::"r"(7 + 2 * wg + hf) : "memory");
        if (lane == 0) {
          tma3_reduce(&maps.o2, sb + OFF_AO + wg * 32768 + 16384 + hf * 8192, chg * 64, 3 * rank, rg * 256 + wg * 128 + hf * 64);
          bulk_commit();
        }
        __syncwarp();
      } else {
        asm volatile("bar.arrive %0, 128;" ::"r"(7 + 2 * wg + hf) : "memory");
      }
    }
    if (lane == 0) bulk_wait0();
  }
}

typedef CUresult (*EncodeFn)(CUtensorMap*, CUtensorMapDataType, cuuint32_t, void*, const cuuint64_t*, const cuuint64_t*, const cuuint32_t*,
                             const cuuint32_t*, CUtensorMapInterleave, CUtensorMapSwizzle, CUtensorMapL2promotion, CUtensorMapFloatOOBfill);

void make_map(EncodeFn enc, CUtensorMap* m, const void* p, uint64_t d0, uint64_t d1, uint64_t d2, uint64_t s1, uint64_t s2, uint32_t b0, uint32_t b1, uint32_t b2,
              CUtensorMapL2promotion promo = CU_TENSOR_MAP_L2_PROMOTION_L2_256B) {
  cuuint64_t dims[3] = {d0, d1, d2}, strides[2] = {s1, s2};
  cuuint32_t box[3] = {b0, b1, b2}, es[3] = {1, 1, 1};
  enc(m, CU_TENSOR_MAP_DATA_TYPE_BFLOAT16, 3, const_cast<void*>(p), dims, strides, box, es, CU_TENSOR_MAP_INTERLEAVE_NONE,
      CU_TENSOR_MAP_SWIZZLE_128B, promo, CU_TENSOR_MAP_FLOAT_OOB_FILL_NONE);
}

}

extern "C" void kernel_launch(void* const* d_in, const int* in_sizes, int n_in, void* d_out, int out_size) {
  (void)in_sizes; (void)n_in; (void)out_size;
  const void *xf = d_in[0], *x = d_in[1], *c = d_in[2], *w1 = d_in[3], *w2 = d_in[4], *wc = d_in[5];
  static EncodeFn enc = nullptr;
  static Ptrs ptrs;
  if (!enc) {
    cudaGetSymbolAddress((void**)&ptrs.V, g_V);
    cudaGetSymbolAddress((void**)&ptrs.U, g_U);
    cudaGetSymbolAddress((void**)&ptrs.flags, g_flags);
    cudaDriverEntryPointQueryResult qr;
    void* fn = nullptr;
    cudaGetDriverEntryPoint("cuTensorMapEncodeTiled", &fn, cudaEnableDefault, &qr);
    enc = (EncodeFn)fn;
    cudaFuncSetAttribute(controlnet_kernel, cudaFuncAttributeMaxDynamicSharedMemorySize, SMEM_BYTES);
  }
  Maps maps;
  make_map(enc, &maps.c, c, 64, 8192, 8, 1024, 128, 64, 64, 1, CU_TENSOR_MAP_L2_PROMOTION_L2_128B);
  make_map(enc, &maps.x, x, 64, 8192, 8, 1024, 128, 64, 64, 1, CU_TENSOR_MAP_L2_PROMOTION_L2_128B);
  make_map(enc, &maps.w1, w1, 64, 512, 8, 1024, 128, 64, 64, 4);
  make_map(enc, &maps.w2, w2, 64, 512, 8, 1024, 128, 64, 64, 4);
  make_map(enc, &maps.w2f, w2, 64, 512, 8, 1024, 128, 64, 64, 2);
  make_map(enc, &maps.wc, wc, 512, 512, 9, 1024, 512 * 1024, 64, 16, 3);
  make_map(enc, &maps.o2, d_out, 512, 4, 2048, 1024, 4096, 64, 1, 64);
  cudaLaunchConfig_t cfg = {};
  cfg.gridDim = dim3(128);
  cfg.blockDim = dim3(512);
  cfg.dynamicSmemBytes = SMEM_BYTES;
  cfg.stream = cudaStreamPerThread;
  cudaLaunchAttribute at[2];
  at[0].id = cudaLaunchAttributeClusterDimension;
  at[0].val.clusterDim.x = 2; at[0].val.clusterDim.y = 1; at[0].val.clusterDim.z = 1;
  at[1].id = cudaLaunchAttributeCooperative;
  at[1].val.cooperative = 1;
  cfg.attrs = at;
  cfg.numAttrs = 2;
  ptrs.xf = (const unsigned char*)xf; ptrs.out = (unsigned char*)d_out;
  ptrs.w1 = (const unsigned char*)w1; ptrs.w2 = (const unsigned char*)w2; ptrs.wc = (const unsigned char*)wc;
  cudaLaunchKernelEx(&cfg, controlnet_kernel, ptrs, maps);
}
```
